```python
import torch

def _softmax(x, axis=-1):
    return torch.softmax(x, dim=axis)

def _gelu(x):
    return torch.nn.functional.gelu(x, approximate='tanh')

def _silu(x):
    return torch.nn.functional.silu(x)

def _sigmoid(x):
    return torch.sigmoid(x)

def _layernorm(x, axis=-1, eps=1e-05):
    m = x.mean(dim=axis, keepdim=True)
    v = x.var(dim=axis, keepdim=True, unbiased=False)
    return (x - m) / torch.sqrt(v + eps)

def _scatter_add(tgt, idx, src, axis=0):
    return tgt.clone().index_add_(axis, idx, src)

def _segment_sum(src, seg, n):
    out = torch.zeros((n,) + src.shape[1:], dtype=src.dtype)
    return out.index_add_(0, seg, src)

def _pad(x, pw):
    flat = tuple((v for pair in reversed(pw) for v in pair))
    return torch.nn.functional.pad(x, flat)
kernel_name = 'adaLN_cond__grouped_kv_mqa__glu_gated_glu__prompt'

def setup_inputs():

    _w = lambda a: (lambda t: t.to(torch.bfloat16) if t.is_floating_point() else t)(torch.as_tensor(a))

    def _A_setup():
        B, S, D, H = (1, 2048, 1024, 32)
        Dh = D // H
        return {'x': _w((lambda *s: torch.randn(*s, dtype=torch.bfloat16) * 0.05)(B, S, D)), 'wq': _w((lambda *s: torch.randn(*s, dtype=torch.bfloat16) * 0.05)(D, H * Dh)), 'wk': _w((lambda *s: torch.randn(*s, dtype=torch.bfloat16) * 0.05)(D, Dh)), 'wv': _w((lambda *s: torch.randn(*s, dtype=torch.bfloat16) * 0.05)(D, Dh)), 'wo': _w((lambda *s: torch.randn(*s, dtype=torch.bfloat16) * 0.05)(H * Dh, D))}
    _A_in = _A_setup()

    def _B_setup():
        B, S, D, F = (1, 2048, 1024, 3584)
        return {'x': _w((lambda *s: torch.randn(*s, dtype=torch.bfloat16) * 0.05)(B, S, D)), 'w_gate': _w((lambda *s: torch.randn(*s, dtype=torch.bfloat16) * 0.05)(D, F)), 'w_up': _w((lambda *s: torch.randn(*s, dtype=torch.bfloat16) * 0.05)(D, F)), 'w_down': _w((lambda *s: torch.randn(*s, dtype=torch.bfloat16) * 0.05)(F, D))}
    _B_in = _B_setup()
    return {'A_x': _A_in['x'], 'A_wq': _A_in['wq'], 'A_wk': _A_in['wk'], 'A_wv': _A_in['wv'], 'A_wo': _A_in['wo'], 'B_x': _B_in['x'], 'B_w_gate': _B_in['w_gate'], 'B_w_up': _B_in['w_up'], 'B_w_down': _B_in['w_down'], 'c': _w((lambda *s: torch.randn(*s, dtype=torch.bfloat16) * 0.2)(1, 1024) * 8.0), 'w_mod': _w((lambda *s: torch.randn(*s, dtype=torch.bfloat16) * 0.2)(1024, 6 * 1024) * 1024 ** (-0.5) * 8.0)}

def reference(A_x, A_wq, A_wk, A_wv, A_wo, B_x, B_w_gate, B_w_up, B_w_down, c, w_mod):

    def _A_ref(x, wq, wk, wv, wo):
        B, S, D = x.shape
        H = 32
        Dh = D // H
        q = (lambda x, *d: x.permute(*d))((x @ wq).reshape(B, S, H, Dh), 0, 2, 1, 3)
        k = x @ wk
        v = x @ wv
        scores = torch.einsum('bhqd,bkd->bhqk', q, k) * Dh ** (-0.5)
        p = _softmax(scores, axis=-1)
        o = torch.einsum('bhqk,bkd->bhqd', p, v)
        return (lambda x, *d: x.permute(*d))(o, 0, 2, 1, 3).reshape(B, S, H * Dh) @ wo

    def _B_ref(x, w_gate, w_up, w_down):
        g = torch.einsum('bsd,df->bsf', x, w_gate)
        u = torch.einsum('bsd,df->bsf', x, w_up)
        h = _sigmoid(g) * u
        return torch.einsum('bsf,fd->bsd', h, w_down)
    x = A_x
    mod = (_silu(c) @ w_mod).reshape(c.shape[0], 6, 1, -1)
    sa, ca, ga, sb, cb, gb = (mod[:, 0].clone(), mod[:, 1].clone(), mod[:, 2].clone(), mod[:, 3].clone(), mod[:, 4].clone(), mod[:, 5].clone())
    h = _layernorm(x, axis=-1) * (1 + ca) + sa
    x = x + ga * _A_ref(h, A_wq, A_wk, A_wv, A_wo)
    h = _layernorm(x, axis=-1) * (1 + cb) + sb
    x = x + gb * _B_ref(h, B_w_gate, B_w_up, B_w_down)
    return x
```

```cpp
#include <cuda_runtime.h>
#include <cuda_bf16.h>
#include <cuda.h>
#include <stdint.h>
#include <type_traits>

typedef __nv_bfloat16 bf16;

template<int TA, int TB> __device__ __forceinline__ void wgmma_m64n128k16_ss(float (&d)[64], uint64_t da, uint64_t db, int scale_d) {
  asm volatile("{\n.reg .pred p;\nsetp.ne.b32 p, %66, 0;\n"
    "wgmma.mma_async.sync.aligned.m64n128k16.f32.bf16.bf16 "
    "{%0, %1, %2, %3, %4, %5, %6, %7, %8, %9, %10, %11, %12, %13, %14, %15, %16, %17, %18, %19, %20, %21, %22, %23, %24, %25, %26, %27, %28, %29, %30, %31, %32, %33, %34, %35, %36, %37, %38, %39, %40, %41, %42, %43, %44, %45, %46, %47, %48, %49, %50, %51, %52, %53, %54, %55, %56, %57, %58, %59, %60, %61, %62, %63}, "
    "%64, %65, p, 1, 1, %67, %68;\n}\n"
    : "+f"(d[0]), "+f"(d[1]), "+f"(d[2]), "+f"(d[3]), "+f"(d[4]), "+f"(d[5]), "+f"(d[6]), "+f"(d[7]), "+f"(d[8]), "+f"(d[9]), "+f"(d[10]), "+f"(d[11]), "+f"(d[12]), "+f"(d[13]), "+f"(d[14]), "+f"(d[15]), "+f"(d[16]), "+f"(d[17]), "+f"(d[18]), "+f"(d[19]), "+f"(d[20]), "+f"(d[21]), "+f"(d[22]), "+f"(d[23]), "+f"(d[24]), "+f"(d[25]), "+f"(d[26]), "+f"(d[27]), "+f"(d[28]), "+f"(d[29]), "+f"(d[30]), "+f"(d[31]), "+f"(d[32]), "+f"(d[33]), "+f"(d[34]), "+f"(d[35]), "+f"(d[36]), "+f"(d[37]), "+f"(d[38]), "+f"(d[39]), "+f"(d[40]), "+f"(d[41]), "+f"(d[42]), "+f"(d[43]), "+f"(d[44]), "+f"(d[45]), "+f"(d[46]), "+f"(d[47]), "+f"(d[48]), "+f"(d[49]), "+f"(d[50]), "+f"(d[51]), "+f"(d[52]), "+f"(d[53]), "+f"(d[54]), "+f"(d[55]), "+f"(d[56]), "+f"(d[57]), "+f"(d[58]), "+f"(d[59]), "+f"(d[60]), "+f"(d[61]), "+f"(d[62]), "+f"(d[63])
    : "l"(da), "l"(db), "r"(scale_d), "n"(TA), "n"(TB));
}
template<int TA, int TB> __device__ __forceinline__ void wgmma_m64n256k16_ss(float (&d)[128], uint64_t da, uint64_t db, int scale_d) {
  asm volatile("{\n.reg .pred p;\nsetp.ne.b32 p, %130, 0;\n"
    "wgmma.mma_async.sync.aligned.m64n256k16.f32.bf16.bf16 "
    "{%0, %1, %2, %3, %4, %5, %6, %7, %8, %9, %10, %11, %12, %13, %14, %15, %16, %17, %18, %19, %20, %21, %22, %23, %24, %25, %26, %27, %28, %29, %30, %31, %32, %33, %34, %35, %36, %37, %38, %39, %40, %41, %42, %43, %44, %45, %46, %47, %48, %49, %50, %51, %52, %53, %54, %55, %56, %57, %58, %59, %60, %61, %62, %63, %64, %65, %66, %67, %68, %69, %70, %71, %72, %73, %74, %75, %76, %77, %78, %79, %80, %81, %82, %83, %84, %85, %86, %87, %88, %89, %90, %91, %92, %93, %94, %95, %96, %97, %98, %99, %100, %101, %102, %103, %104, %105, %106, %107, %108, %109, %110, %111, %112, %113, %114, %115, %116, %117, %118, %119, %120, %121, %122, %123, %124, %125, %126, %127}, "
    "%128, %129, p, 1, 1, %131, %132;\n}\n"
    : "+f"(d[0]), "+f"(d[1]), "+f"(d[2]), "+f"(d[3]), "+f"(d[4]), "+f"(d[5]), "+f"(d[6]), "+f"(d[7]), "+f"(d[8]), "+f"(d[9]), "+f"(d[10]), "+f"(d[11]), "+f"(d[12]), "+f"(d[13]), "+f"(d[14]), "+f"(d[15]), "+f"(d[16]), "+f"(d[17]), "+f"(d[18]), "+f"(d[19]), "+f"(d[20]), "+f"(d[21]), "+f"(d[22]), "+f"(d[23]), "+f"(d[24]), "+f"(d[25]), "+f"(d[26]), "+f"(d[27]), "+f"(d[28]), "+f"(d[29]), "+f"(d[30]), "+f"(d[31]), "+f"(d[32]), "+f"(d[33]), "+f"(d[34]), "+f"(d[35]), "+f"(d[36]), "+f"(d[37]), "+f"(d[38]), "+f"(d[39]), "+f"(d[40]), "+f"(d[41]), "+f"(d[42]), "+f"(d[43]), "+f"(d[44]), "+f"(d[45]), "+f"(d[46]), "+f"(d[47]), "+f"(d[48]), "+f"(d[49]), "+f"(d[50]), "+f"(d[51]), "+f"(d[52]), "+f"(d[53]), "+f"(d[54]), "+f"(d[55]), "+f"(d[56]), "+f"(d[57]), "+f"(d[58]), "+f"(d[59]), "+f"(d[60]), "+f"(d[61]), "+f"(d[62]), "+f"(d[63]), "+f"(d[64]), "+f"(d[65]), "+f"(d[66]), "+f"(d[67]), "+f"(d[68]), "+f"(d[69]), "+f"(d[70]), "+f"(d[71]), "+f"(d[72]), "+f"(d[73]), "+f"(d[74]), "+f"(d[75]), "+f"(d[76]), "+f"(d[77]), "+f"(d[78]), "+f"(d[79]), "+f"(d[80]), "+f"(d[81]), "+f"(d[82]), "+f"(d[83]), "+f"(d[84]), "+f"(d[85]), "+f"(d[86]), "+f"(d[87]), "+f"(d[88]), "+f"(d[89]), "+f"(d[90]), "+f"(d[91]), "+f"(d[92]), "+f"(d[93]), "+f"(d[94]), "+f"(d[95]), "+f"(d[96]), "+f"(d[97]), "+f"(d[98]), "+f"(d[99]), "+f"(d[100]), "+f"(d[101]), "+f"(d[102]), "+f"(d[103]), "+f"(d[104]), "+f"(d[105]), "+f"(d[106]), "+f"(d[107]), "+f"(d[108]), "+f"(d[109]), "+f"(d[110]), "+f"(d[111]), "+f"(d[112]), "+f"(d[113]), "+f"(d[114]), "+f"(d[115]), "+f"(d[116]), "+f"(d[117]), "+f"(d[118]), "+f"(d[119]), "+f"(d[120]), "+f"(d[121]), "+f"(d[122]), "+f"(d[123]), "+f"(d[124]), "+f"(d[125]), "+f"(d[126]), "+f"(d[127])
    : "l"(da), "l"(db), "r"(scale_d), "n"(TA), "n"(TB));
}
template<int TA, int TB> __device__ __forceinline__ void wgmma_m64n16k16_ss(float (&d)[8], uint64_t da, uint64_t db, int scale_d) {
  asm volatile("{\n.reg .pred p;\nsetp.ne.b32 p, %10, 0;\n"
    "wgmma.mma_async.sync.aligned.m64n16k16.f32.bf16.bf16 "
    "{%0, %1, %2, %3, %4, %5, %6, %7}, "
    "%8, %9, p, 1, 1, %11, %12;\n}\n"
    : "+f"(d[0]), "+f"(d[1]), "+f"(d[2]), "+f"(d[3]), "+f"(d[4]), "+f"(d[5]), "+f"(d[6]), "+f"(d[7])
    : "l"(da), "l"(db), "r"(scale_d), "n"(TA), "n"(TB));
}
template<int TB> __device__ __forceinline__ void wgmma_m64n64k16_rs(float (&d)[32], uint32_t a0, uint32_t a1, uint32_t a2, uint32_t a3, uint64_t db, int scale_d) {
  asm volatile("{\n.reg .pred p;\nsetp.ne.b32 p, %37, 0;\n"
    "wgmma.mma_async.sync.aligned.m64n64k16.f32.bf16.bf16 "
    "{%0, %1, %2, %3, %4, %5, %6, %7, %8, %9, %10, %11, %12, %13, %14, %15, %16, %17, %18, %19, %20, %21, %22, %23, %24, %25, %26, %27, %28, %29, %30, %31}, "
    "{%32, %33, %34, %35}, %36, p, 1, 1, %38;\n}\n"
    : "+f"(d[0]), "+f"(d[1]), "+f"(d[2]), "+f"(d[3]), "+f"(d[4]), "+f"(d[5]), "+f"(d[6]), "+f"(d[7]), "+f"(d[8]), "+f"(d[9]), "+f"(d[10]), "+f"(d[11]), "+f"(d[12]), "+f"(d[13]), "+f"(d[14]), "+f"(d[15]), "+f"(d[16]), "+f"(d[17]), "+f"(d[18]), "+f"(d[19]), "+f"(d[20]), "+f"(d[21]), "+f"(d[22]), "+f"(d[23]), "+f"(d[24]), "+f"(d[25]), "+f"(d[26]), "+f"(d[27]), "+f"(d[28]), "+f"(d[29]), "+f"(d[30]), "+f"(d[31])
    : "r"(a0), "r"(a1), "r"(a2), "r"(a3), "l"(db), "r"(scale_d), "n"(TB));
}
template<int TB> __device__ __forceinline__ void wgmma_m64n40k16_rs(float (&d)[20], uint32_t a0, uint32_t a1, uint32_t a2, uint32_t a3, uint64_t db, int scale_d) {
  asm volatile("{\n.reg .pred p;\nsetp.ne.b32 p, %25, 0;\n"
    "wgmma.mma_async.sync.aligned.m64n40k16.f32.bf16.bf16 "
    "{%0, %1, %2, %3, %4, %5, %6, %7, %8, %9, %10, %11, %12, %13, %14, %15, %16, %17, %18, %19}, "
    "{%20, %21, %22, %23}, %24, p, 1, 1, %26;\n}\n"
    : "+f"(d[0]), "+f"(d[1]), "+f"(d[2]), "+f"(d[3]), "+f"(d[4]), "+f"(d[5]), "+f"(d[6]), "+f"(d[7]), "+f"(d[8]), "+f"(d[9]), "+f"(d[10]), "+f"(d[11]), "+f"(d[12]), "+f"(d[13]), "+f"(d[14]), "+f"(d[15]), "+f"(d[16]), "+f"(d[17]), "+f"(d[18]), "+f"(d[19])
    : "r"(a0), "r"(a1), "r"(a2), "r"(a3), "l"(db), "r"(scale_d), "n"(TB));
}

constexpr int SEQ = 2048, DM = 1024, FF = 3584, MODN = 6144;
constexpr int NTHREADS = 384, NWORK = 128, NCTA = 132;
constexpr uint32_t SLOT = 16384, NSLOT = 12;
constexpr uint32_t OFF_STG = NSLOT * SLOT;
constexpr uint32_t OFF_FULL = OFF_STG + 32768;
constexpr uint32_t OFF_EMPTY = OFF_FULL + 8 * NSLOT;
constexpr uint32_t OFF_STF = OFF_EMPTY + 8 * NSLOT;
constexpr uint32_t OFF_STE = OFF_STF + 16;
constexpr uint32_t OFF_AUX = OFF_STE + 16;
constexpr uint32_t OFF_VEC = OFF_FULL + 256;
constexpr uint32_t SMEM_BYTES = OFF_VEC + 2048 + 512;
static_assert(SMEM_BYTES <= 232448, "shared memory budget");

constexpr int F_MOD = 0, F_MOD2 = 1, F_H1 = 2, F_KV = 18, F_O = 34, F_ST = 66, F_H2 = 98, F_HH = 226, F_EPOCH = 290, F_COUNT = 291;

constexpr uint32_t ORD_Q = 0x321054;
constexpr uint32_t ORD_A = 0x1032;
constexpr uint32_t ORD_O = 0x10324;
constexpr uint32_t ORD_G = 0x3210;
constexpr uint32_t ORD_D = 0x543210;

#define IDLE_NS 200
#define NPOLY 3

__device__ float g_mod[MODN];
__device__ __align__(1024) bf16 g_h1[SEQ * DM];
__device__ __align__(1024) bf16 g_k[SEQ * 32];
__device__ __align__(1024) bf16 g_vt[40 * SEQ];
__device__ __align__(1024) bf16 g_o[SEQ * DM];
__device__ __align__(1024) bf16 g_h2[SEQ * DM];
__device__ __align__(1024) bf16 g_hh[SEQ * FF];
__device__ __align__(16) uint32_t g_mod1[2 * DM];
__device__ __align__(16) uint2 g_stats[16 * 8 * 128];
__device__ uint32_t g_flags[F_COUNT * 32];

struct Params {
  CUtensorMap wq, wo, wd, wg2, wu2;
  CUtensorMap wg1, wu1;
  CUtensorMap wk, wv;
  CUtensorMap h1, ob, h2, hh, xm;
  CUtensorMap obs, h2s, hhs, outs;
  CUtensorMap kb, vt;
  CUtensorMap wm;
  const bf16* x;
  const bf16* c;
  const bf16* wmod;
};

template <int V> struct IC { static constexpr int value = V; __host__ __device__ constexpr operator int() const { return V; } };
template <int I, int N, typename F> __device__ __forceinline__ void static_for(F&& f) {
  if constexpr (I < N) { f(IC<I>{}); static_for<I + 1, N>(f); }
}
__device__ __forceinline__ uint32_t opaque(uint32_t x) { uint32_t r; asm volatile("mov.u32 %0, %1;" : "=r"(r) : "r"(x)); return r; }
__device__ __forceinline__ void mbar_init(uint32_t bar, uint32_t cnt) { asm volatile("mbarrier.init.shared::cta.b64 [%0], %1;" ::"r"(bar), "r"(cnt)); }
__device__ __forceinline__ void mbar_expect_tx(uint32_t bar, uint32_t bytes) { asm volatile("mbarrier.arrive.expect_tx.shared::cta.b64 _, [%0], %1;" ::"r"(bar), "r"(bytes) : "memory"); }
__device__ __forceinline__ void mbar_arrive(uint32_t bar) { asm volatile("mbarrier.arrive.shared::cta.b64 _, [%0];" ::"r"(bar) : "memory"); }
__device__ __forceinline__ bool mbar_try(uint32_t bar, uint32_t parity) {
  uint32_t ok;
  asm volatile("{\n.reg .pred p;\nmbarrier.try_wait.parity.shared::cta.b64 p, [%1], %2;\nselp.u32 %0,1,0,p;\n}" : "=r"(ok) : "r"(bar), "r"(parity) : "memory");
  return ok;
}
__device__ __forceinline__ void mbar_wait_slow(uint32_t bar, uint32_t parity) {
#pragma unroll 1
  for (int i = 0; i < (1 << 24); i++) if (mbar_try(bar, parity)) return;
  __trap();
}
__device__ __forceinline__ void mbar_wait_idle(uint32_t bar, uint32_t parity) {
#pragma unroll 1
  for (int i = 0; i < (1 << 22); i++) { if (mbar_try(bar, parity)) return; __nanosleep(IDLE_NS); }
  __trap();
}
__device__ __forceinline__ void mbar_wait(uint32_t bar, uint32_t parity) { if (!mbar_try(bar, parity)) mbar_wait_slow(bar, parity); }

__device__ __forceinline__ void tma_load(uint32_t dst, const CUtensorMap* m, uint32_t bar, int c0, int c1) {
  asm volatile("cp.async.bulk.tensor.2d.shared::cluster.global.mbarrier::complete_tx::bytes [%0], [%1, {%3, %4}], [%2];"
               ::"r"(dst), "l"(m), "r"(bar), "r"(c0), "r"(c1) : "memory");
}
__device__ __forceinline__ void tma_load3(uint32_t dst, const CUtensorMap* m, uint32_t bar, int c0, int c1, int c2) {
  asm volatile("cp.async.bulk.tensor.3d.shared::cluster.global.mbarrier::complete_tx::bytes [%0], [%1, {%3, %4, %5}], [%2];"
               ::"r"(dst), "l"(m), "r"(bar), "r"(c0), "r"(c1), "r"(c2) : "memory");
}
__device__ __forceinline__ uint64_t policy_evict_first() { uint64_t p; asm volatile("createpolicy.fractional.L2::evict_first.b64 %0, 1.0;" : "=l"(p)); return p; }
__device__ __forceinline__ void tma_load_s(uint32_t dst, const CUtensorMap* m, uint32_t bar, int c0, int c1, uint64_t pol) {
  asm volatile("cp.async.bulk.tensor.2d.shared::cluster.global.mbarrier::complete_tx::bytes.L2::cache_hint [%0], [%1, {%3, %4}], [%2], %5;"
               ::"r"(dst), "l"(m), "r"(bar), "r"(c0), "r"(c1), "l"(pol) : "memory");
}
__device__ __forceinline__ void tma_load3_s(uint32_t dst, const CUtensorMap* m, uint32_t bar, int c0, int c1, int c2, uint64_t pol) {
  asm volatile("cp.async.bulk.tensor.3d.shared::cluster.global.mbarrier::complete_tx::bytes.L2::cache_hint [%0], [%1, {%3, %4, %5}], [%2], %6;"
               ::"r"(dst), "l"(m), "r"(bar), "r"(c0), "r"(c1), "r"(c2), "l"(pol) : "memory");
}
__device__ __forceinline__ bool elect_one() {
  uint32_t p;
  asm volatile("{\n.reg .pred P;\nelect.sync _|P, 0xffffffff;\nselp.u32 %0,1,0,P;\n}" : "=r"(p));
  return p;
}
__device__ __forceinline__ void tma_store(const CUtensorMap* m, uint32_t src, int c0, int c1) {
  asm volatile("cp.async.bulk.tensor.2d.global.shared::cta.bulk_group [%0, {%2, %3}], [%1];" ::"l"(m), "r"(src), "r"(c0), "r"(c1) : "memory");
}
__device__ __forceinline__ void tma_prefetch(const CUtensorMap* m, int c0, int c1) {
  asm volatile("cp.async.bulk.prefetch.tensor.2d.L2.global [%0, {%1, %2}];" ::"l"(m), "r"(c0), "r"(c1) : "memory");
}
__device__ __forceinline__ void tma_prefetch3(const CUtensorMap* m, int c0, int c1, int c2) {
  asm volatile("cp.async.bulk.prefetch.tensor.3d.L2.global [%0, {%1, %2, %3}];" ::"l"(m), "r"(c0), "r"(c1), "r"(c2) : "memory");
}
__device__ __forceinline__ void bulk_commit() { asm volatile("cp.async.bulk.commit_group;" ::: "memory"); }
__device__ __forceinline__ void bulk_wait_read() { asm volatile("cp.async.bulk.wait_group.read 0;" ::: "memory"); }
__device__ __forceinline__ void bulk_wait_all() { asm volatile("cp.async.bulk.wait_group 0;" ::: "memory"); }
__device__ __forceinline__ void fence_async_smem() { asm volatile("fence.proxy.async.shared::cta;" ::: "memory"); }
__device__ __forceinline__ void fence_async_global() { asm volatile("fence.proxy.async.global;" ::: "memory"); }
__device__ __forceinline__ void wg_fence() { asm volatile("wgmma.fence.sync.aligned;" ::: "memory"); }
__device__ __forceinline__ void wg_commit() { asm volatile("wgmma.commit_group.sync.aligned;" ::: "memory"); }
template <int N> __device__ __forceinline__ void wg_wait() { asm volatile("wgmma.wait_group.sync.aligned %0;" ::"n"(N) : "memory"); }
template <int R> __device__ __forceinline__ void reg_alloc() { asm volatile("setmaxnreg.inc.sync.aligned.u32 %0;" ::"n"(R)); }
template <int R> __device__ __forceinline__ void reg_dealloc() { asm volatile("setmaxnreg.dec.sync.aligned.u32 %0;" ::"n"(R)); }
__device__ __forceinline__ void bar_sync(int id, int n) { asm volatile("bar.sync %0, %1;" ::"r"(id), "r"(n) : "memory"); }
__device__ __forceinline__ uint64_t dsc(uint32_t lo, uint32_t hi) { uint64_t r; asm("mov.b64 %0, {%1,%2};" : "=l"(r) : "r"(lo), "r"(hi)); return r; }
constexpr uint32_t HI_128 = (1024 >> 4) | (1u << 30);
constexpr uint32_t HI_64 = (512 >> 4) | (2u << 30);

template <int N> __device__ __forceinline__ void fence_regs(float (&r)[N]) {
#pragma unroll
  for (int i = 0; i < N; i++) asm volatile("" : "+f"(r[i])::"memory");
}
template <int N> __device__ __forceinline__ void fence_regs(uint32_t (&r)[N]) {
#pragma unroll
  for (int i = 0; i < N; i++) asm volatile("" : "+r"(r[i])::"memory");
}
__device__ __forceinline__ void fence4(uint32_t* p) { asm volatile("" : "+r"(p[0]), "+r"(p[1]), "+r"(p[2]), "+r"(p[3])::"memory"); }

__device__ __forceinline__ uint32_t* flag_ptr(int i) { return g_flags + i * 32; }
__device__ __forceinline__ void flag_signal(int i) {
  asm volatile("fence.acq_rel.gpu;\nred.relaxed.gpu.global.add.u32 [%0], 1;" ::"l"(flag_ptr(i)) : "memory");
}
__device__ __forceinline__ uint32_t load_epoch() {
  uint32_t v;
  asm volatile("ld.relaxed.gpu.global.u32 %0, [%1];" : "=r"(v) : "l"(flag_ptr(F_EPOCH)) : "memory");
  return v + 1;
}
__device__ __forceinline__ void flag_wait(int i, uint32_t target) {
  const uint32_t* p = flag_ptr(i);
#pragma unroll 1
  for (int it = 0; it < (1 << 22); it++) {
    uint32_t v;
    asm volatile("ld.acquire.gpu.global.u32 %0, [%1];" : "=r"(v) : "l"(p) : "memory");
    if ((int32_t)(v - target) >= 0) return;
  }
  __trap();
}

__device__ __forceinline__ void st_tagged(uint32_t* p, float v) { asm volatile("st.relaxed.gpu.global.u32 [%0], %1;" ::"l"(p), "r"(__float_as_uint(v) | 1u) : "memory"); }
__device__ __forceinline__ void st_tagged2(uint2* p, float a, float b) {
  asm volatile("st.relaxed.gpu.global.v2.u32 [%0], {%1,%2};" ::"l"(p), "r"(__float_as_uint(a) | 1u), "r"(__float_as_uint(b) | 1u) : "memory");
}
__device__ __forceinline__ uint4 ld_tagged4(const uint32_t* p) {
  uint4 v;
#pragma unroll 1
  for (int it = 0; it < (1 << 22); it++) {
    asm volatile("ld.relaxed.gpu.global.v4.u32 {%0,%1,%2,%3}, [%4];" : "=r"(v.x), "=r"(v.y), "=r"(v.z), "=r"(v.w) : "l"(p) : "memory");
    if (v.x & v.y & v.z & v.w & 1u) return v;
  }
  __trap();
  return v;
}
__device__ __forceinline__ float2 ld_tagged2(const uint2* p) {
  uint2 v;
#pragma unroll 1
  for (int it = 0; it < (1 << 22); it++) {
    asm volatile("ld.relaxed.gpu.global.v2.u32 {%0,%1}, [%2];" : "=r"(v.x), "=r"(v.y) : "l"(p) : "memory");
    if (v.x & v.y & 1u) return make_float2(__uint_as_float(v.x), __uint_as_float(v.y));
  }
  __trap();
  return make_float2(0.f, 0.f);
}
__device__ __forceinline__ float ex2(float x) { float y; asm("ex2.approx.ftz.f32 %0, %1;" : "=f"(y) : "f"(x)); return y; }
__device__ __forceinline__ float tanh_fast(float x) { float y; asm("tanh.approx.f32 %0, %1;" : "=f"(y) : "f"(x)); return y; }
__device__ __forceinline__ uint32_t pack_bf16(float lo, float hi) { uint32_t r; asm("cvt.rn.bf16x2.f32 %0, %1, %2;" : "=r"(r) : "f"(hi), "f"(lo)); return r; }
__device__ __forceinline__ float bf_lo(uint32_t v) { return __uint_as_float(v << 16); }
__device__ __forceinline__ float bf_hi(uint32_t v) { return __uint_as_float(v & 0xffff0000u); }
__device__ __forceinline__ float round_bf16(float x) { return bf_lo(pack_bf16(x, 0.f)); }
__device__ __forceinline__ float fma_sat(float a, float b, float c) { float r; asm("fma.rn.sat.f32 %0, %1, %2, %3;" : "=f"(r) : "f"(a), "f"(b), "f"(c)); return r; }
__device__ __forceinline__ void stsm4(uint32_t addr, uint32_t a, uint32_t b, uint32_t c, uint32_t d) {
  asm volatile("stmatrix.sync.aligned.m8n8.x4.shared.b16 [%0], {%1,%2,%3,%4};" ::"r"(addr), "r"(a), "r"(b), "r"(c), "r"(d) : "memory");
}
__device__ __forceinline__ float lds32(uint32_t a) { float v; asm volatile("ld.shared.f32 %0, [%1];" : "=f"(v) : "r"(a)); return v; }
__device__ __forceinline__ float2 lds64(uint32_t a) { float2 v; asm volatile("ld.shared.v2.f32 {%0,%1}, [%2];" : "=f"(v.x), "=f"(v.y) : "r"(a)); return v; }
__device__ __forceinline__ void sts32(uint32_t a, float v) { asm volatile("st.shared.f32 [%0], %1;" ::"r"(a), "f"(v) : "memory"); }
__device__ __forceinline__ void sts128(uint32_t a, uint4 v) { asm volatile("st.shared.v4.b32 [%0], {%1,%2,%3,%4};" ::"r"(a), "r"(v.x), "r"(v.y), "r"(v.z), "r"(v.w) : "memory"); }

#define PROF(cond, k)
#define PROFC(cond, k)

struct Producer {
  uint32_t sb, emask;
  uint64_t pol;
  template <int BAR> __device__ __forceinline__ void acquire() {
    mbar_wait(sb + OFF_EMPTY + 8 * BAR, (emask >> BAR) & 1);
    emask ^= 1u << BAR;
  }
  template <int S0> __device__ __forceinline__ void arm(uint32_t bytes) { mbar_expect_tx(sb + OFF_FULL + 8 * S0, bytes); }
  template <int S0> __device__ __forceinline__ void begin(uint32_t bytes) { acquire<S0>(); arm<S0>(bytes); }
  template <int S0> __device__ __forceinline__ void loadA(const CUtensorMap* m, int k0, int row0) {
    tma_load(sb + S0 * SLOT, m, sb + OFF_FULL + 8 * S0, k0, row0);
  }
  template <int S0> __device__ __forceinline__ void loadB(const CUtensorMap* m, int nblk, int k0) {
    tma_load3_s(sb + (S0 + 1) * SLOT, m, sb + OFF_FULL + 8 * S0, 0, k0, nblk, pol);
  }
};
__host__ __device__ constexpr int ord(uint32_t o, int i) { return (o >> (4 * i)) & 15; }

__device__ __forceinline__ void producer_role(const Params& p, uint32_t sb, int mt, int j, int cta) {
  Producer P{sb, 0xFFFu, policy_evict_first()};
  const uint32_t ep = load_epoch();
  auto wait_and_fence = [&](int flag, uint32_t n) { flag_wait(flag, n * ep); fence_async_global(); };
  const int row0 = mt * 128;
  mbar_expect_tx(sb + OFF_AUX, 32768);
  for (int q = 0; q < 4; q++) tma_load(sb + OFF_STG + q * 8192, &p.wm, sb + OFF_AUX, cta * 16, q * 256);
  mbar_wait(sb + OFF_AUX, 0);
  static_for<0, 4>([&](auto Q) {
    constexpr int q = decltype(Q)::value;
    P.template begin<2 * q>(32768);
    tma_load(sb + 2 * q * SLOT, &p.wk, sb + OFF_FULL + 16 * q, 0, 256 * q);
    tma_load(sb + (2 * q + 1) * SLOT, &p.wv, sb + OFF_FULL + 16 * q, 0, 256 * q);
  });
  static_for<0, 2>([&](auto I) { constexpr int s = 2 * ord(ORD_Q, I); P.begin<s>(32768); P.loadB<s>(&p.wq, j * 2, I * 64); });
  wait_and_fence(F_H1 + mt, 8);
  static_for<0, 2>([&](auto I) { P.loadA<2 * ord(ORD_Q, I)>(&p.h1, I * 64, row0); });
  static_for<2, 16>([&](auto I) {
    constexpr int s = 2 * ord(ORD_Q, I % 6);
    P.begin<s>(32768); P.loadB<s>(&p.wq, j * 2, I * 64); P.loadA<s>(&p.h1, I * 64, row0);
  });
  PROF(true, 16);
#pragma unroll 1
  for (int r = 0; r < 16; r++) {
    static_for<0, 4>([&](auto Q) {
      constexpr int s = 2 * ord(ORD_A, Q);
      const int t = (4 * r + Q) & 15;
      P.begin<s>(8192 + 2 * 5120);
      if (r < 4) wait_and_fence(F_KV + t, 8);
      const uint32_t fb = sb + OFF_FULL + 8 * s, d = sb + s * SLOT;
      tma_load(d, &p.kb, fb, 0, t * 128);
      tma_load(d + 8192, &p.vt, fb, t * 128, 0);
      tma_load(d + 13312, &p.vt, fb, t * 128 + 64, 0);
    });
    if (r == 8) tma_prefetch3(&p.wo, 0, mt * 64, j * 2);
    if (r == 10) { tma_prefetch3(&p.wg2, 0, mt * 64, j * 7); tma_prefetch3(&p.wu2, 0, mt * 64, j * 7); }
    if (r == 13) {
      P.begin<10>(32768);
      tma_load(sb + 10 * SLOT, &p.xm, sb + OFF_FULL + 80, j * 128, row0);
      tma_load(sb + 11 * SLOT, &p.xm, sb + OFF_FULL + 80, j * 128 + 64, row0);
      constexpr int so = 2 * ord(ORD_O, 0);
      P.begin<so>(32768); P.loadB<so>(&p.wo, j * 2, 0);
    }
  }
  wait_and_fence(F_O + 2 * mt, 16);
  P.loadA<2 * ord(ORD_O, 0)>(&p.ob, 0, row0);
  static_for<1, 8>([&](auto I) {
    constexpr int s = 2 * ord(ORD_O, I % 5), k0 = 128 * I;
    P.begin<s>(32768); P.loadB<s>(&p.wo, j * 2, k0); P.loadA<s>(&p.ob, k0, row0);
  });
  static_for<8, 10>([&](auto I) { constexpr int s = 2 * ord(ORD_O, I % 5); P.begin<s>(32768); P.loadB<s>(&p.wo, j * 2, 128 * (I - 8) + 64); });
  wait_and_fence(F_O + 2 * mt + 1, 16);
  static_for<8, 10>([&](auto I) { P.loadA<2 * ord(ORD_O, I % 5)>(&p.ob, 128 * (I - 8) + 64, row0); });
  static_for<10, 16>([&](auto I) {
    constexpr int s = 2 * ord(ORD_O, I % 5), k0 = 128 * (I - 8) + 64;
    P.begin<s>(32768); P.loadB<s>(&p.wo, j * 2, k0); P.loadA<s>(&p.ob, k0, row0);
  });
  PROF(true, 17);
  auto gu_b = [&](auto Q, int t, int k0) {
    constexpr int s = 3 * Q;
    const uint32_t fb = sb + OFF_FULL + 8 * s, d = sb + (s + 1) * SLOT;
    const int fblk = j * 7 + t * 2;
    if (t < 3) {
      P.arm<s>(49152);
      tma_load3_s(d, &p.wg2, fb, 0, k0, fblk, P.pol); tma_load3_s(d + 16384, &p.wu2, fb, 0, k0, fblk, P.pol);
    } else {
      P.arm<s>(32768);
      tma_load_s(d, &p.wg1, fb, fblk * 64, k0, P.pol); tma_load_s(d + 8192, &p.wu1, fb, fblk * 64, k0, P.pol);
    }
  };
  using I0 = IC<0>; using I1 = IC<1>; using I2 = IC<2>; using I3 = IC<3>;
  P.acquire<0>(); P.acquire<2>(); gu_b(I0{}, 0, 0);
  P.acquire<4>(); P.emask &= ~(1u << 3); gu_b(I1{}, 0, 64);
  P.acquire<6>(); P.acquire<8>(); gu_b(I2{}, 0, 128);
  wait_and_fence(F_H2 + 8 * mt, 2);
  P.loadA<0>(&p.h2, 0, row0); P.loadA<3>(&p.h2, 64, row0);
  wait_and_fence(F_H2 + 8 * mt + 1, 2);
  P.loadA<6>(&p.h2, 128, row0);
  P.acquire<10>(); P.emask &= ~(1u << 9); gu_b(I3{}, 0, 192); P.loadA<9>(&p.h2, 192, row0);
#pragma unroll 1
  for (int r = 1; r < 16; r++) {
    const int t = r >> 2;
    static_for<0, 4>([&](auto Q) {
      const int kb = ((r & 3) << 2) + Q;
      P.acquire<3 * Q>();
      gu_b(Q, t, kb * 64);
      if (r < 4 && (Q & 1) == 0) wait_and_fence(F_H2 + 8 * mt + (kb >> 1), 2);
      P.loadA<3 * Q>(&p.h2, kb * 64, row0);
    });
    if (r < 12 && (r & 3) == 1) {
      const int fblk = j * 7 + (t + 1) * 2;
      if (t < 2) { tma_prefetch3(&p.wg2, 0, mt * 64, fblk); tma_prefetch3(&p.wu2, 0, mt * 64, fblk); }
      else { tma_prefetch(&p.wg1, fblk * 64, mt * 64); tma_prefetch(&p.wu1, fblk * 64, mt * 64); }
    }
    if (r >= 8 && r < 12 && (mt + 16 * (r - 8)) < 56) tma_prefetch3(&p.wd, 0, (mt + 16 * (r - 8)) * 64, j * 2);
    if (r == 7) wait_and_fence(F_HH + 4 * mt, 16);
    if (r == 11) wait_and_fence(F_HH + 4 * mt + 1, 16);
  }
  PROF(true, 18);
  auto dkb = [&](int i) { return i < 48 ? 7 * ((i & 15) >> 1) + 2 * (i >> 4) + (i & 1) : 7 * (i - 48) + 6; };
  P.acquire<0>(); P.arm<0>(32768); P.loadB<0>(&p.wd, j * 2, dkb(0) * 64);
  wait_and_fence(F_HH + 4 * mt + 2, 16);
  P.loadA<0>(&p.hh, dkb(0) * 64, row0);
  P.acquire<3>(); P.arm<2>(32768); P.loadB<2>(&p.wd, j * 2, dkb(1) * 64); P.loadA<2>(&p.hh, dkb(1) * 64, row0);
  P.arm<4>(32768); P.loadB<4>(&p.wd, j * 2, dkb(2) * 64); P.loadA<4>(&p.hh, dkb(2) * 64, row0);
  P.acquire<6>(); P.arm<6>(32768); P.loadB<6>(&p.wd, j * 2, dkb(3) * 64); P.loadA<6>(&p.hh, dkb(3) * 64, row0);
  P.acquire<9>(); P.arm<8>(32768); P.loadB<8>(&p.wd, j * 2, dkb(4) * 64); P.loadA<8>(&p.hh, dkb(4) * 64, row0);
  P.arm<10>(32768); P.loadB<10>(&p.wd, j * 2, dkb(5) * 64); P.loadA<10>(&p.hh, dkb(5) * 64, row0);
#pragma unroll 1
  for (int r = 1; r < 8; r++)
    static_for<0, 6>([&](auto Q) {
      const int k0 = dkb(6 * r + Q) * 64;
      P.begin<2 * Q>(32768); P.loadB<2 * Q>(&p.wd, j * 2, k0); P.loadA<2 * Q>(&p.hh, k0, row0);
    });
  static_for<0, 3>([&](auto Q) { P.begin<2 * Q>(32768); P.loadB<2 * Q>(&p.wd, j * 2, (7 * Q + 6) * 64); });
  wait_and_fence(F_HH + 4 * mt + 3, 16);
  static_for<0, 3>([&](auto Q) { P.loadA<2 * Q>(&p.hh, (7 * Q + 6) * 64, row0); });
  static_for<3, 8>([&](auto Q) {
    constexpr int s = 2 * (Q % 6);
    P.begin<s>(32768); P.loadB<s>(&p.wd, j * 2, (7 * Q + 6) * 64); P.loadA<s>(&p.hh, (7 * Q + 6) * 64, row0);
  });
  PROF(true, 19);
}

__device__ __forceinline__ void store_role(const Params& p, uint32_t sb, int w, int mt, int j) {
  const uint32_t full = sb + OFF_STF + 8 * w, empty = sb + OFF_STE + 8 * w, stg = sb + OFF_STG + w * 16384;
  const int row = mt * 128 + w * 64;
  uint32_t ph = 0;
  auto job = [&](const CUtensorMap* m, int col, int box0, int nbox, bool rel, int flag) {
    mbar_wait_idle(full, ph); ph ^= 1;
    for (int b = 0; b < nbox; b++) tma_store(m, stg + (box0 + b) * 8192, col + b * 64, row);
    bulk_commit();
    if (rel) { bulk_wait_read(); mbar_arrive(empty); }
    if (flag >= 0) { bulk_wait_all(); flag_signal(flag); }
  };
  job(&p.obs, j * 128, 0, 1, false, F_O + 2 * mt);
  job(&p.obs, j * 128 + 64, 1, 1, true, F_O + 2 * mt + 1);
  job(&p.h2s, j * 128, 0, 2, true, F_H2 + 8 * mt + j);
  for (int t = 0; t < 3; t++) job(&p.hhs, j * 448 + t * 128, 0, 2, true, F_HH + 4 * mt + t);
  job(&p.hhs, j * 448 + 384, 0, 1, true, F_HH + 4 * mt + 3);
  job(&p.outs, j * 128, 0, 2, false, -1);
  bulk_wait_all();
}

__device__ __forceinline__ void signal_role(uint32_t sb, int mt) {
  mbar_wait_idle(sb + OFF_AUX + 16, 0);
  flag_signal(F_H1 + mt);
  mbar_wait_idle(sb + OFF_AUX + 24, 0);
  flag_signal(F_KV + mt);
}

struct Cons {
  uint32_t sb, fmask, stph;
  int cw, lane, warp;
  bool leader;
  __device__ __forceinline__ void wait_full(int slot) {
    mbar_wait(sb + OFF_FULL + 8 * slot, (fmask >> slot) & 1);
    fmask ^= 1u << slot;
  }
  __device__ __forceinline__ void release(int s0) { if (leader) mbar_arrive(sb + OFF_EMPTY + 8 * s0); }
  __device__ __forceinline__ void stg_acquire() { mbar_wait(sb + OFF_STE + 8 * cw, stph); stph ^= 1; }
  __device__ __forceinline__ void stg_publish() {
    fence_async_smem();
    __syncwarp();
    if (lane == 0) mbar_arrive(sb + OFF_STF + 8 * cw);
  }
  __device__ __forceinline__ uint32_t stg_addr(int cb16) const {
    int row = warp * 16 + (lane & 7) + ((lane >> 3) & 1) * 8;
    int chunk = (cb16 & 3) * 2 + (lane >> 4);
    return sb + OFF_STG + cw * 16384 + (cb16 >> 2) * 8192 + row * 128 + ((chunk ^ (row & 7)) << 4);
  }
};

template <int N, int SPS, uint32_t ORD, int NORD>
__device__ __forceinline__ void gemm_loop(Cons& c, float (&acc)[N / 2], int nst, int idx0) {
  const uint32_t abase = ((c.sb + c.cw * 8192) >> 4) | (1u << 16);
  const uint32_t bbase = ((c.sb + SLOT) >> 4) | ((8192u >> 4) << 16);
  int idx = idx0, prev = 0;
#pragma unroll 1
  for (int i = 0; i < nst; i++) {
    const int s = SPS * ((ORD >> (4 * idx)) & 15);
    c.wait_full(s);
    wg_fence();
#pragma unroll
    for (int k = 0; k < 4; k++) {
      const uint64_t da = dsc(abase + s * (SLOT >> 4) + k * 2, HI_128), db = dsc(bbase + s * (SLOT >> 4) + k * 128, HI_128);
      if constexpr (N == 256) wgmma_m64n256k16_ss<0, 1>(acc, da, db, (i | k) != 0);
      else wgmma_m64n128k16_ss<0, 1>(acc, da, db, (i | k) != 0);
    }
    wg_commit();
    if (i > 0) { wg_wait<1>(); c.release(prev); }
    prev = s;
    if (++idx == NORD) idx = 0;
  }
  wg_wait<0>();
  c.release(prev);
  fence_regs(acc);
}

__device__ __forceinline__ float exp2_fma(float s, float a, float b) {
  const float MAGIC = 12582912.f - 125.f;
  float y = fma_sat(s, a, b);
  float t = fmaf(y, 253.f, MAGIC);
  float u = t - MAGIC;
  float f = fmaf(y, 253.f, -u);
  float q = fmaf(f, 0.0551716685295105f, 0.2426111251115799f);
  q = fmaf(q, f, 0.6932609677314758f);
  q = fmaf(q, f, 0.9999280571937561f);
  return __uint_as_float(__float_as_uint(q) + (__float_as_uint(t) << 23));
}
constexpr float SM_C = 0.17677669529663687f * 1.4426950408889634f;
struct SoftmaxRow { float mc0, mc1, a, b0, b1; };
template <int G>
__device__ __forceinline__ void softmax_grp(const float (&S)[32], uint32_t (&P)[16], const SoftmaxRow& r) {
  constexpr int order[16] = {1, 12, 6, 9, 3, 14, 4, 11, 0, 13, 5, 8, 2, 15, 7, 10};
  float e[8];
#pragma unroll
  for (int k = 0; k < 8; k++) {
    bool poly = false;
#pragma unroll
    for (int q = 0; q < NPOLY; q++) if (order[q] == k + 8 * (G & 1)) poly = true;
    const bool hi = (k >> 1) & 1;
    e[k] = poly ? exp2_fma(S[8 * G + k], r.a, hi ? r.b1 : r.b0) : ex2(fmaf(S[8 * G + k], SM_C, -(hi ? r.mc1 : r.mc0)));
  }
#pragma unroll
  for (int k = 0; k < 4; k++) P[4 * G + k] = pack_bf16(e[2 * k], e[2 * k + 1]);
}

__device__ __forceinline__ void hmma(float (&d)[4], const uint32_t* a, uint32_t b0, uint32_t b1) {
  asm volatile("mma.sync.aligned.m16n8k16.row.col.f32.bf16.bf16.f32 {%0,%1,%2,%3},{%4,%5,%6,%7},{%8,%9},{%0,%1,%2,%3};"
               : "+f"(d[0]), "+f"(d[1]), "+f"(d[2]), "+f"(d[3]) : "r"(a[0]), "r"(a[1]), "r"(a[2]), "r"(a[3]), "r"(b0), "r"(b1));
}
__device__ __forceinline__ void attention_exact(const uint32_t (&q)[8], float (&o16)[20], float& lo0, float& lo1, int lane) {
  float O[4][4] = {}, m0 = -INFINITY, m1 = -INFINITY, l0 = 0.f, l1 = 0.f;
  const uint32_t* K = reinterpret_cast<const uint32_t*>(g_k);
  const uint32_t* V = reinterpret_cast<const uint32_t*>(g_vt);
  const int g = lane >> 2, t = lane & 3;
#pragma unroll 1
  for (int k0 = 0; k0 < SEQ; k0 += 16) {
    float s[2][4] = {};
#pragma unroll
    for (int nb = 0; nb < 2; nb++)
#pragma unroll
      for (int kk = 0; kk < 2; kk++) {
        const uint32_t* kp = K + (k0 + nb * 8 + g) * 16 + kk * 8 + t;
        hmma(s[nb], &q[4 * kk], __ldcg(kp), __ldcg(kp + 4));
      }
    float n0 = fmaxf(fmaxf(s[0][0], s[0][1]), fmaxf(s[1][0], s[1][1])), n1 = fmaxf(fmaxf(s[0][2], s[0][3]), fmaxf(s[1][2], s[1][3]));
    n0 = fmaxf(n0, __shfl_xor_sync(~0u, n0, 1)); n0 = fmaxf(n0, __shfl_xor_sync(~0u, n0, 2));
    n1 = fmaxf(n1, __shfl_xor_sync(~0u, n1, 1)); n1 = fmaxf(n1, __shfl_xor_sync(~0u, n1, 2));
    n0 = fmaxf(n0, m0); n1 = fmaxf(n1, m1);
    const float r0 = exp2f((m0 - n0) * SM_C), r1 = exp2f((m1 - n1) * SM_C);
    m0 = n0; m1 = n1;
    uint32_t pa[4];
#pragma unroll
    for (int nb = 0; nb < 2; nb++) {
      pa[2 * nb] = pack_bf16(exp2f((s[nb][0] - m0) * SM_C), exp2f((s[nb][1] - m0) * SM_C));
      pa[2 * nb + 1] = pack_bf16(exp2f((s[nb][2] - m1) * SM_C), exp2f((s[nb][3] - m1) * SM_C));
    }
    l0 = l0 * r0 + bf_lo(pa[0]) + bf_hi(pa[0]) + bf_lo(pa[2]) + bf_hi(pa[2]);
    l1 = l1 * r1 + bf_lo(pa[1]) + bf_hi(pa[1]) + bf_lo(pa[3]) + bf_hi(pa[3]);
#pragma unroll
    for (int nb = 0; nb < 4; nb++) {
      O[nb][0] *= r0; O[nb][1] *= r0; O[nb][2] *= r1; O[nb][3] *= r1;
      const uint32_t* vp = V + ((nb * 8 + g) * SEQ + k0) / 2 + t;
      hmma(O[nb], pa, __ldcg(vp), __ldcg(vp + 4));
    }
  }
  l0 += __shfl_xor_sync(~0u, l0, 1); l0 += __shfl_xor_sync(~0u, l0, 2);
  l1 += __shfl_xor_sync(~0u, l1, 1); l1 += __shfl_xor_sync(~0u, l1, 2);
#pragma unroll
  for (int nb = 0; nb < 4; nb++)
#pragma unroll
    for (int e = 0; e < 4; e++) o16[4 * nb + e] = O[nb][e];
  lo0 = l0; lo1 = l1;
}

__device__ __forceinline__ void attention_head(Cons& c, const uint32_t (&q)[8], int hh) {
  const uint32_t base0 = (c.sb >> 4) | (1u << 16);
  constexpr uint32_t STG = 2 * SLOT >> 4;
  float S0[32], S1[32], Oa[20];
  uint32_t P0[16], P1[16];
  auto qka = [&](float (&S)[32], uint32_t lo) { wgmma_m64n64k16_rs<0>(S, q[0], q[1], q[2], q[3], dsc(lo, HI_64), 0); };
  auto qkb = [&](float (&S)[32], uint32_t lo) { wgmma_m64n64k16_rs<0>(S, q[4], q[5], q[6], q[7], dsc(lo + 2, HI_64), 1); };
  auto pv = [&](uint32_t (&P)[16], int kk, uint32_t lo) { wgmma_m64n40k16_rs<0>(Oa, P[4 * kk], P[4 * kk + 1], P[4 * kk + 2], P[4 * kk + 3], dsc(lo + kk * 2, HI_128), 1); };
  constexpr int P_FIRST = ORD_A & 15, P_LAST = (ORD_A >> 12) & 15;
  c.wait_full(2 * P_FIRST);
  {
    const uint32_t kb = base0 + P_FIRST * STG;
    wg_fence(); qka(S0, kb); qkb(S0, kb); qka(S1, kb + 256); qkb(S1, kb + 256); wg_commit(); wg_wait<0>();
    fence_regs(S0); fence_regs(S1);
  }
  float m0 = S0[0], m1 = S0[2];
#pragma unroll
  for (int i = 0; i < 8; i++) {
    m0 = fmaxf(m0, fmaxf(fmaxf(S0[4 * i], S0[4 * i + 1]), fmaxf(S1[4 * i], S1[4 * i + 1])));
    m1 = fmaxf(m1, fmaxf(fmaxf(S0[4 * i + 2], S0[4 * i + 3]), fmaxf(S1[4 * i + 2], S1[4 * i + 3])));
  }
  m0 = fmaxf(m0, __shfl_xor_sync(~0u, m0, 1)); m0 = fmaxf(m0, __shfl_xor_sync(~0u, m0, 2));
  m1 = fmaxf(m1, __shfl_xor_sync(~0u, m1, 1)); m1 = fmaxf(m1, __shfl_xor_sync(~0u, m1, 2));
  SoftmaxRow r;
  r.mc0 = fmaf(m0, SM_C, 40.f); r.mc1 = fmaf(m1, SM_C, 40.f);
  r.a = SM_C * (1.f / 253.f); r.b0 = (125.f - r.mc0) * (1.f / 253.f); r.b1 = (125.f - r.mc1) * (1.f / 253.f);
#pragma unroll
  for (int i = 0; i < 20; i++) Oa[i] = 0.f;
#pragma unroll
  for (int i = 0; i < 16; i++) P1[i] = 0u;
  fence_regs(Oa); fence_regs(P1);
  auto tile = [&](auto ST, int turn) {
    constexpr int st = decltype(ST)::value;
    constexpr int pc = (ORD_A >> (4 * st)) & 15, pp = (ORD_A >> (4 * ((st + 3) & 3))) & 15, pn = (ORD_A >> (4 * ((st + 1) & 3))) & 15;
    const bool first = (st == 0) && (turn == 0), last = (st == 3) && (turn == 3);
    const uint32_t kb = base0 + pc * STG, vb = kb + 512;
    const uint32_t vprev = first ? vb : base0 + pp * STG + 512;
    const uint32_t kn = last ? kb : base0 + pn * STG;
    const uint32_t nbar = c.sb + OFF_FULL + 16 * pn, npar = (c.fmask >> (2 * pn)) & 1;
    bool ok = true;
    if (!last) { ok = mbar_try(nbar, npar); c.fmask ^= 1u << (2 * pn); }
    softmax_grp<0>(S0, P0, r); fence_regs(S1); fence4(P1 + 12); wg_fence(); pv(P1, 3, vprev + 320); qka(S1, kb + 256);
    softmax_grp<1>(S0, P0, r); fence4(P0); wg_fence(); qkb(S1, kb + 256); wg_commit(); pv(P0, 0, vb);
    softmax_grp<2>(S0, P0, r); fence4(P0 + 4); wg_fence(); pv(P0, 1, vb);
    softmax_grp<3>(S0, P0, r); fence4(P0 + 8); wg_fence(); pv(P0, 2, vb); wg_commit();
    wg_wait<1>(); fence_regs(S1); fence_regs(P1);
    if (!first) c.release(2 * pp);
    if (!ok) mbar_wait_slow(nbar, npar);
    softmax_grp<0>(S1, P1, r); fence_regs(S0); fence4(P0 + 12); wg_fence(); pv(P0, 3, vb); qka(S0, kn);
    softmax_grp<1>(S1, P1, r); fence4(P1); wg_fence(); qkb(S0, kn); wg_commit(); pv(P1, 0, vb + 320);
    softmax_grp<2>(S1, P1, r); fence4(P1 + 4); wg_fence(); pv(P1, 1, vb + 320);
    softmax_grp<3>(S1, P1, r); fence4(P1 + 8); wg_fence(); pv(P1, 2, vb + 320); wg_commit();
    wg_wait<1>(); fence_regs(S0); fence_regs(P0);
  };
#pragma unroll 1
  for (int turn = 0; turn < 4; turn++) {
    tile(IC<0>{}, turn); tile(IC<1>{}, turn);
    tile(IC<2>{}, turn); tile(IC<3>{}, turn);
  }
  fence4(P1 + 12); wg_fence(); pv(P1, 3, base0 + P_LAST * STG + 512 + 320); wg_commit();
  wg_wait<0>(); fence_regs(Oa);
  c.release(2 * P_LAST);
  float l0 = __shfl_sync(~0u, Oa[16], c.lane & ~3), l1 = __shfl_sync(~0u, Oa[18], c.lane & ~3);
  bool bad = !(l0 < 1e30f) || !(l1 < 1e30f);
#pragma unroll
  for (int i = 0; i < 16; i++) bad |= !(fabsf(Oa[i]) <= 3.0e38f);
  if (__any_sync(~0u, bad)) {
    attention_exact(q, Oa, l0, l1, c.lane);
  }
  const float i0 = 1.f / l0, i1 = 1.f / l1;
#pragma unroll
  for (int h2 = 0; h2 < 2; h2++) {
    const int a = 8 * h2;
    stsm4(c.stg_addr(hh * 2 + h2), pack_bf16(Oa[a] * i0, Oa[a + 1] * i0), pack_bf16(Oa[a + 2] * i1, Oa[a + 3] * i1),
          pack_bf16(Oa[a + 4] * i0, Oa[a + 5] * i0), pack_bf16(Oa[a + 6] * i1, Oa[a + 7] * i1));
  }
}

template <int NB>
__device__ __forceinline__ void glu_epilogue(Cons& c, const float (&acc)[NB * 64]) {
  c.stg_acquire();
#pragma unroll
  for (int b = 0; b < NB; b++)
#pragma unroll
    for (int cb = 0; cb < 4; cb++) {
      uint32_t v[4];
#pragma unroll
      for (int e = 0; e < 4; e++) {
        const int ig = b * 32 + cb * 8 + 2 * e, iu = ig + NB * 32;
        const float h0 = fmaf(tanh_fast(0.5f * acc[ig]), 0.5f, 0.5f) * acc[iu];
        const float h1 = fmaf(tanh_fast(0.5f * acc[ig + 1]), 0.5f, 0.5f) * acc[iu + 1];
        v[e] = pack_bf16(h0, h1);
      }
      stsm4(c.stg_addr(b * 4 + cb), v[0], v[1], v[2], v[3]);
    }
  c.stg_publish();
}

__device__ __forceinline__ float silu_bf16(float v) { return round_bf16(__fdividef(v, 1.f + __expf(-v))); }
__device__ __forceinline__ uint4 ldg_l2line(const void* a) {
  uint4 v;
  asm volatile("ld.global.nc.L1::no_allocate.L2::128B.v4.u32 {%0,%1,%2,%3}, [%4];" : "=r"(v.x), "=r"(v.y), "=r"(v.z), "=r"(v.w) : "l"(a));
  return v;
}
__device__ __forceinline__ uint4 lds128(uint32_t a) {
  uint4 v;
  asm volatile("ld.shared.v4.b32 {%0,%1,%2,%3}, [%4];" : "=r"(v.x), "=r"(v.y), "=r"(v.z), "=r"(v.w) : "r"(a));
  return v;
}
__device__ __forceinline__ void unpack8(const uint4& v, float (&f)[8]) {
  f[0] = bf_lo(v.x); f[1] = bf_hi(v.x); f[2] = bf_lo(v.y); f[3] = bf_hi(v.y);
  f[4] = bf_lo(v.z); f[5] = bf_hi(v.z); f[6] = bf_lo(v.w); f[7] = bf_hi(v.w);
}

__device__ __forceinline__ void consumer_role(const Params& p, uint32_t sb, int cw, int mt, int j, int cta) {
  const int tid = threadIdx.x - 128, lane = tid & 31, warp8 = tid >> 5;
  Cons c{sb, 0u, 0u, cw, lane, warp8 & 3, (tid & 127) == 0};
  const bool lead0 = tid == 0;
  const uint32_t ep = lead0 ? load_epoch() : 0u;
  PROF(lead0, 0); PROFC(lead0, 20);

  {
    uint4 xv[2][4];
    float cv[8];
    const int rg = tid >> 1, hf = tid & 1;
    const int r0 = mt * 128 + j * 16 + warp8 * 2;
#pragma unroll
    for (int i = 0; i < 8; i++) cv[i] = __bfloat162float(p.c[rg + 128 * i]);
#pragma unroll
    for (int rr = 0; rr < 2; rr++)
#pragma unroll
      for (int i = 0; i < 4; i++) xv[rr][i] = __ldg(reinterpret_cast<const uint4*>(p.x + (size_t)(r0 + rr) * DM + i * 256 + lane * 8));
#pragma unroll
    for (int i = 0; i < 8; i++) cv[i] = silu_bf16(cv[i]);
    float acc[8] = {};
    mbar_wait(sb + OFF_AUX, 0);
#pragma unroll
    for (int i = 0; i < 8; i++) {
      float f[8]; unpack8(lds128(sb + OFF_STG + (rg + 128 * i) * 32 + hf * 16), f);
#pragma unroll
      for (int e = 0; e < 8; e++) acc[e] = fmaf(cv[i], f[e], acc[e]);
    }
#pragma unroll
    for (int e = 0; e < 8; e++)
#pragma unroll
      for (int o = 2; o < 32; o <<= 1) acc[e] += __shfl_xor_sync(~0u, acc[e], o);
    if (lane < 2)
#pragma unroll
      for (int e = 0; e < 8; e++) sts32(sb + OFF_VEC + (warp8 * 16 + lane * 8 + e) * 4, acc[e]);
    PROF(lead0, 26);
    bar_sync(1, 256);
    if (tid < 16) {
      float s = 0.f;
#pragma unroll
      for (int w = 0; w < 8; w++) s += lds32(sb + OFF_VEC + (w * 16 + tid) * 4);
      st_tagged(g_mod1 + cta * 16 + tid, round_bf16(s));
    }
    float mean[2], rstd[2];
#pragma unroll
    for (int rr = 0; rr < 2; rr++) {
      float s = 0.f;
#pragma unroll
      for (int i = 0; i < 4; i++) { float f[8]; unpack8(xv[rr][i], f);
#pragma unroll
        for (int e = 0; e < 8; e++) s += f[e]; }
#pragma unroll
      for (int o = 1; o < 32; o <<= 1) s += __shfl_xor_sync(~0u, s, o);
      mean[rr] = s * (1.f / DM);
      float v = 0.f;
#pragma unroll
      for (int i = 0; i < 4; i++) { float f[8]; unpack8(xv[rr][i], f);
#pragma unroll
        for (int e = 0; e < 8; e++) { const float d = f[e] - mean[rr]; v = fmaf(d, d, v); } }
#pragma unroll
      for (int o = 1; o < 32; o <<= 1) v += __shfl_xor_sync(~0u, v, o);
      rstd[rr] = rsqrtf(v * (1.f / DM) + 1e-5f);
    }
    PROF(lead0, 1);
#pragma unroll
    for (int i = 0; i < 2; i++) {
      const uint4 v = ld_tagged4(g_mod1 + (i * 256 + tid) * 4);
      sts128(sb + OFF_STG + (i * 256 + tid) * 16, make_uint4(v.x & ~1u, v.y & ~1u, v.z & ~1u, v.w & ~1u));
    }
    bar_sync(1, 256);
    PROF(lead0, 2);
    uint4 mv[4][4];
#pragma unroll
    for (int i = 0; i < 4; i++) {
      const uint32_t a = sb + OFF_STG + (i * 256 + lane * 8) * 4;
      mv[i][0] = lds128(a); mv[i][1] = lds128(a + 16); mv[i][2] = lds128(a + 4096); mv[i][3] = lds128(a + 4096 + 16);
    }
    bar_sync(1, 256);
#pragma unroll
    for (int i = 0; i < 4; i++) {
      const int col = i * 256 + lane * 8;
      const float sa[8] = {__uint_as_float(mv[i][0].x), __uint_as_float(mv[i][0].y), __uint_as_float(mv[i][0].z), __uint_as_float(mv[i][0].w),
                           __uint_as_float(mv[i][1].x), __uint_as_float(mv[i][1].y), __uint_as_float(mv[i][1].z), __uint_as_float(mv[i][1].w)};
      const float ca[8] = {__uint_as_float(mv[i][2].x), __uint_as_float(mv[i][2].y), __uint_as_float(mv[i][2].z), __uint_as_float(mv[i][2].w),
                           __uint_as_float(mv[i][3].x), __uint_as_float(mv[i][3].y), __uint_as_float(mv[i][3].z), __uint_as_float(mv[i][3].w)};
#pragma unroll
      for (int rr = 0; rr < 2; rr++) {
        float f[8]; unpack8(xv[rr][i], f);
        float h[8];
#pragma unroll
        for (int e = 0; e < 8; e++) h[e] = fmaf((f[e] - mean[rr]) * rstd[rr], 1.f + ca[e], sa[e]);
        const uint4 o = make_uint4(pack_bf16(h[0], h[1]), pack_bf16(h[2], h[3]), pack_bf16(h[4], h[5]), pack_bf16(h[6], h[7]));
        *reinterpret_cast<uint4*>(g_h1 + (size_t)(r0 + rr) * DM + col) = o;
        const int row = warp8 * 2 + rr;
        sts128(sb + OFF_STG + (i * 4 + (lane >> 3)) * 2048 + row * 128 + (((lane & 7) ^ (row & 7)) << 4), o);
      }
    }
    PROF(lead0, 27);
    fence_async_smem();
    fence_async_global();
    bar_sync(1, 256);
    PROF(lead0, 28);
    if (lead0) mbar_arrive(sb + OFF_AUX + 16);
    PROF(lead0, 3);
  }

  {
    float d[8];
    const uint32_t abase = (sb >> 4) | ((SLOT >> 4) << 16), bbase = ((sb + OFF_STG) >> 4) | (1u << 16);
#pragma unroll 1
    for (int q = 0; q < 4; q++) {
      c.wait_full(2 * q);
      if (cw == 0) {
        wg_fence();
#pragma unroll
        for (int k = 0; k < 16; k++)
          wgmma_m64n16k16_ss<1, 0>(d, dsc(abase + q * 2 * (SLOT >> 4) + k * 64, HI_64),
                                   dsc(bbase + (q * 4 + (k >> 2)) * 128 + (k & 3) * 2, HI_128), (q | k) != 0);
        wg_commit(); wg_wait<0>();
      }
      c.release(2 * q);
    }
    PROF(lead0, 29);
    if (cw == 0) {
      fence_regs(d);
      const int tok0 = mt * 128 + j * 16, g = lane >> 2, t = lane & 3;
      if (c.warp < 2) {
#pragma unroll
        for (int e = 0; e < 8; e++) {
          const int m = c.warp * 16 + g + ((e >> 1) & 1) * 8, n = (e >> 2) * 8 + 2 * t + (e & 1);
          g_k[(tok0 + n) * 32 + m] = __float2bfloat16(d[e]);
        }
      } else {
#pragma unroll
        for (int e = 0; e < 4; e++) {
          const int m = (c.warp - 2) * 16 + g + (e & 1) * 8, n = (e >> 1) * 8 + 2 * t;
          *reinterpret_cast<uint32_t*>(g_vt + m * SEQ + tok0 + n) = pack_bf16(d[2 * e], d[2 * e + 1]);
        }
        if (c.warp == 2 && lane < 16) {
          const uint32_t one = lane < 2 ? 0x3f803f80u : 0u;
          *reinterpret_cast<uint4*>(g_vt + (32 + (lane >> 1)) * SEQ + tok0 + (lane & 1) * 8) = make_uint4(one, one, one, one);
        }
      }
      fence_async_global();
      bar_sync(2, 128);
      if (c.leader) mbar_arrive(sb + OFF_AUX + 24);
    }
  }
  PROF(lead0, 4);

  uint32_t qf[4][8];
  {
    float acc[64];
    gemm_loop<128, 2, ORD_Q, 6>(c, acc, 16, 0);
#pragma unroll
    for (int h = 0; h < 4; h++)
#pragma unroll
      for (int i = 0; i < 8; i++) qf[h][i] = pack_bf16(acc[16 * h + 2 * i], acc[16 * h + 2 * i + 1]);
  }
  PROF(lead0, 5); PROFC(lead0, 21);

#pragma unroll 1
  for (int hh = 0; hh < 4; hh++) {
    uint32_t q[8];
#pragma unroll
    for (int i = 0; i < 8; i++) q[i] = hh == 0 ? qf[0][i] : hh == 1 ? qf[1][i] : hh == 2 ? qf[2][i] : qf[3][i];
    attention_head(c, q, hh);
    if (hh & 1) c.stg_publish();
  }
  PROF(lead0, 6); PROFC(lead0, 22);

  const int g8 = lane >> 2, t4 = lane & 3;
  uint32_t x1p[32];
  {
    if (lead0) flag_wait(F_MOD2, (NCTA - NWORK) * ep);
    bar_sync(1, 256);
    for (int i = tid; i < 512; i += 256) {
      const int v = i >> 7, col = j * 128 + (i & 127);
      const float m = __ldcg(g_mod + (v + 2) * DM + col);
      sts32(sb + OFF_VEC + i * 4, v == 2 ? 1.f + m : m);
    }
    bar_sync(1, 256);
    float acc[64];
    c.wait_full(10);
    gemm_loop<128, 2, ORD_O, 5>(c, acc, 16, 0);
    PROF(lead0, 7);
    uint32_t xin[32];
    {
      const int r = cw * 64 + c.warp * 16 + g8;
#pragma unroll
      for (int nb = 0; nb < 16; nb++) {
        const uint32_t a = sb + (10 + (nb >> 3)) * SLOT + r * 128 + (((nb & 7) ^ (r & 7)) << 4) + t4 * 4;
        xin[2 * nb] = __float_as_uint(lds32(a)); xin[2 * nb + 1] = __float_as_uint(lds32(a + 1024));
      }
    }
    float s0 = 0.f, s1 = 0.f;
#pragma unroll
    for (int nb = 0; nb < 16; nb++) {
      const float2 ga = lds64(sb + OFF_VEC + (nb * 8 + t4 * 2) * 4);
      x1p[2 * nb] = pack_bf16(fmaf(ga.x, acc[4 * nb], bf_lo(xin[2 * nb])), fmaf(ga.y, acc[4 * nb + 1], bf_hi(xin[2 * nb])));
      x1p[2 * nb + 1] = pack_bf16(fmaf(ga.x, acc[4 * nb + 2], bf_lo(xin[2 * nb + 1])), fmaf(ga.y, acc[4 * nb + 3], bf_hi(xin[2 * nb + 1])));
      s0 += bf_lo(x1p[2 * nb]) + bf_hi(x1p[2 * nb]);
      s1 += bf_lo(x1p[2 * nb + 1]) + bf_hi(x1p[2 * nb + 1]);
    }
    __syncwarp();
    bar_sync(2 + cw, 128);
    c.release(10);
    s0 += __shfl_xor_sync(~0u, s0, 1); s0 += __shfl_xor_sync(~0u, s0, 2);
    s1 += __shfl_xor_sync(~0u, s1, 1); s1 += __shfl_xor_sync(~0u, s1, 2);
    const float pm0 = s0 * (1.f / 128), pm1 = s1 * (1.f / 128);
    float v0 = 0.f, v1 = 0.f;
#pragma unroll
    for (int nb = 0; nb < 16; nb++) {
      float d;
      d = bf_lo(x1p[2 * nb]) - pm0; v0 = fmaf(d, d, v0); d = bf_hi(x1p[2 * nb]) - pm0; v0 = fmaf(d, d, v0);
      d = bf_lo(x1p[2 * nb + 1]) - pm1; v1 = fmaf(d, d, v1); d = bf_hi(x1p[2 * nb + 1]) - pm1; v1 = fmaf(d, d, v1);
    }
    v0 += __shfl_xor_sync(~0u, v0, 1); v0 += __shfl_xor_sync(~0u, v0, 2);
    v1 += __shfl_xor_sync(~0u, v1, 1); v1 += __shfl_xor_sync(~0u, v1, 2);
    const int lrow = cw * 64 + c.warp * 16 + g8;
    if (t4 == 0) {
      st_tagged2(&g_stats[(mt * 8 + j) * 128 + lrow], pm0, v0);
      st_tagged2(&g_stats[(mt * 8 + j) * 128 + lrow + 8], pm1, v1);
    }
    float mu[2], rs[2];
#pragma unroll
    for (int rr = 0; rr < 2; rr++) {
      const float2 a = ld_tagged2(&g_stats[(mt * 8 + 2 * t4) * 128 + lrow + 8 * rr]), b = ld_tagged2(&g_stats[(mt * 8 + 2 * t4 + 1) * 128 + lrow + 8 * rr]);
      float m = a.x + b.x;
      m += __shfl_xor_sync(~0u, m, 1); m += __shfl_xor_sync(~0u, m, 2);
      m *= 0.125f;
      float q = a.y + b.y + 128.f * ((a.x - m) * (a.x - m) + (b.x - m) * (b.x - m));
      q += __shfl_xor_sync(~0u, q, 1); q += __shfl_xor_sync(~0u, q, 2);
      mu[rr] = m; rs[rr] = rsqrtf(q * (1.f / DM) + 1e-5f);
    }
    PROF(lead0, 8);
    c.stg_acquire();
#pragma unroll
    for (int cb = 0; cb < 8; cb++) {
      uint32_t v[4];
#pragma unroll
      for (int h = 0; h < 2; h++) {
        const int nb = 2 * cb + h;
        const float2 sh = lds64(sb + OFF_VEC + 512 + (nb * 8 + t4 * 2) * 4), sc = lds64(sb + OFF_VEC + 1024 + (nb * 8 + t4 * 2) * 4);
        v[2 * h] = pack_bf16(fmaf((bf_lo(x1p[2 * nb]) - mu[0]) * rs[0], sc.x, sh.x), fmaf((bf_hi(x1p[2 * nb]) - mu[0]) * rs[0], sc.y, sh.y));
        v[2 * h + 1] = pack_bf16(fmaf((bf_lo(x1p[2 * nb + 1]) - mu[1]) * rs[1], sc.x, sh.x), fmaf((bf_hi(x1p[2 * nb + 1]) - mu[1]) * rs[1], sc.y, sh.y));
      }
      stsm4(c.stg_addr(cb), v[0], v[1], v[2], v[3]);
    }
    c.stg_publish();
  }
  PROF(lead0, 9); PROFC(lead0, 23);

#pragma unroll 1
  for (int t = 0; t < 3; t++) {
    float acc[128];
    gemm_loop<256, 3, ORD_G, 4>(c, acc, 16, 0);
    glu_epilogue<2>(c, acc);
    PROF(lead0, 10 + t);
  }
  {
    float acc[64];
    gemm_loop<128, 3, ORD_G, 4>(c, acc, 16, 0);
    glu_epilogue<1>(c, acc);
  }
  PROF(lead0, 13); PROFC(lead0, 24);

  {
    float acc[64];
    gemm_loop<128, 2, ORD_D, 6>(c, acc, 56, 0);
    PROF(lead0, 14);
    c.stg_acquire();
#pragma unroll
    for (int cb = 0; cb < 8; cb++) {
      uint32_t v[4];
#pragma unroll
      for (int h = 0; h < 2; h++) {
        const int nb = 2 * cb + h;
        const float2 gb = lds64(sb + OFF_VEC + 1536 + (nb * 8 + t4 * 2) * 4);
        v[2 * h] = pack_bf16(fmaf(gb.x, acc[4 * nb], bf_lo(x1p[2 * nb])), fmaf(gb.y, acc[4 * nb + 1], bf_hi(x1p[2 * nb])));
        v[2 * h + 1] = pack_bf16(fmaf(gb.x, acc[4 * nb + 2], bf_lo(x1p[2 * nb + 1])), fmaf(gb.y, acc[4 * nb + 3], bf_hi(x1p[2 * nb + 1])));
      }
      stsm4(c.stg_addr(cb), v[0], v[1], v[2], v[3]);
    }
    c.stg_publish();
  }
  if (tid < 16) g_mod1[cta * 16 + tid] = 0u;
  if (tid < 128) g_stats[(mt * 8 + j) * 128 + tid] = make_uint2(0u, 0u);
  PROF(lead0, 15); PROFC(lead0, 25);
}

__device__ __forceinline__ void helper_role(const Params& p, uint32_t sb, int hidx) {
  constexpr int HST = 6, ROWS = 16;
  const int tid = threadIdx.x;
  const uint32_t full = sb + OFF_FULL, empty = sb + OFF_EMPTY, sil = sb + OFF_STG;
  if (tid == 0) {
    for (int s = 0; s < HST; s++) { mbar_init(full + 8 * s, 1); mbar_init(empty + 8 * s, 8); }
    asm volatile("fence.mbarrier_init.release.cluster;" ::: "memory");
  }
  for (int i = tid; i < DM; i += NTHREADS) sts32(sil + i * 4, silu_bf16(__bfloat162float(p.c[i])));
  __syncthreads();
  const bf16* src = p.wmod + 2 * DM + hidx * 1024;
  if (tid >= 256 && tid < 288) {
    if (elect_one()) for (int i = 0; i < DM / ROWS; i++) {
      const int s = i % HST;
      mbar_wait(empty + 8 * s, ((i / HST) & 1) ^ 1);
      mbar_expect_tx(full + 8 * s, ROWS * 2048);
      for (int r = 0; r < ROWS; r++)
        asm volatile("cp.async.bulk.shared::cluster.global.mbarrier::complete_tx::bytes [%0], [%1], 2048, [%2];"
                     ::"r"(sb + s * 32768 + r * 2048), "l"(src + (size_t)(i * ROWS + r) * MODN), "r"(full + 8 * s) : "memory");
    }
  } else if (tid < 256) {
    const int cg = tid & 127, rh = tid >> 7;
    float acc[8] = {};
#pragma unroll 1
    for (int i = 0; i < DM / ROWS; i++) {
      const int s = i % HST;
      mbar_wait(full + 8 * s, (i / HST) & 1);
#pragma unroll
      for (int r = 0; r < ROWS / 2; r++) {
        const int row = rh * (ROWS / 2) + r;
        uint4 w;
        asm volatile("ld.shared.v4.b32 {%0,%1,%2,%3}, [%4];" : "=r"(w.x), "=r"(w.y), "=r"(w.z), "=r"(w.w) : "r"(sb + s * 32768 + row * 2048 + cg * 16));
        const float sv = lds32(sil + (i * ROWS + row) * 4);
        float f[8]; unpack8(w, f);
#pragma unroll
        for (int e = 0; e < 8; e++) acc[e] = fmaf(sv, f[e], acc[e]);
      }
      __syncwarp();
      if ((tid & 31) == 0) mbar_arrive(empty + 8 * s);
    }
    const uint32_t red = sil + 4096;
    if (rh == 1)
#pragma unroll
      for (int e = 0; e < 8; e++) sts32(red + (cg * 8 + e) * 4, acc[e]);
    bar_sync(1, 256);
    if (rh == 0)
#pragma unroll
      for (int e = 0; e < 8; e++) g_mod[2 * DM + hidx * 1024 + cg * 8 + e] = round_bf16(acc[e] + lds32(red + (cg * 8 + e) * 4));
    bar_sync(1, 256);
    if (tid == 0) flag_signal(F_MOD2);
    PROF(tid == 0, 0);
  }
}

__global__ void __launch_bounds__(NTHREADS, 1) adaln_block_kernel(const __grid_constant__ Params p) {
  PROF(threadIdx.x == 0, 30);
  extern __shared__ __align__(1024) uint8_t smem[];
  const uint32_t sb = opaque((uint32_t)__cvta_generic_to_shared(smem));
  const int tid = threadIdx.x, cta = blockIdx.x;
  const int wg = __shfl_sync(~0u, tid >> 7, 0);
  if (cta >= NWORK) {
    helper_role(p, sb, cta - NWORK);
  } else {
    if (tid == 0) {
      for (int s = 0; s < (int)NSLOT; s++) { mbar_init(sb + OFF_FULL + 8 * s, 1); mbar_init(sb + OFF_EMPTY + 8 * s, 2); }
      for (int w = 0; w < 2; w++) { mbar_init(sb + OFF_STF + 8 * w, 4); mbar_init(sb + OFF_STE + 8 * w, 1); }
      for (int w = 0; w < 4; w++) mbar_init(sb + OFF_AUX + 8 * w, 1);
      asm volatile("fence.mbarrier_init.release.cluster;" ::: "memory");
    }
    __syncthreads();
    const int grp = cta >> 3, r = cta & 7;
    const int mt = (grp >> 2) * 4 + (r >> 1), j = (grp & 3) * 2 + (r & 1);
    if (wg == 0) {
      reg_dealloc<40>();
      const int warp = __shfl_sync(~0u, tid >> 5, 0);
      if (warp == 0) { if (elect_one()) producer_role(p, sb, mt, j, cta); }
      else if (warp <= 2) { if (elect_one()) store_role(p, sb, warp - 1, mt, j); }
      else { if (elect_one()) signal_role(sb, mt); }
    } else {
      reg_alloc<232>();
      consumer_role(p, sb, wg - 1, mt, j, cta);
    }
  }
  __syncthreads();
  PROF(tid == 0, 31);
  if (cta == 0 && tid == 0) *flag_ptr(F_EPOCH) = load_epoch();
}

typedef CUresult (*EncodeFn)(CUtensorMap*, CUtensorMapDataType, cuuint32_t, void*, const cuuint64_t*, const cuuint64_t*, const cuuint32_t*,
                             const cuuint32_t*, CUtensorMapInterleave, CUtensorMapSwizzle, CUtensorMapL2promotion, CUtensorMapFloatOOBfill);

static void make_map(EncodeFn enc, CUtensorMap* m, const void* ptr, uint64_t inner, uint64_t outer, uint32_t bi, uint32_t bo, CUtensorMapSwizzle sw) {
  cuuint64_t dims[2] = {inner, outer}, strides[1] = {inner * 2};
  cuuint32_t box[2] = {bi, bo}, es[2] = {1, 1};
  enc(m, CU_TENSOR_MAP_DATA_TYPE_BFLOAT16, 2, const_cast<void*>(ptr), dims, strides, box, es, CU_TENSOR_MAP_INTERLEAVE_NONE, sw,
      CU_TENSOR_MAP_L2_PROMOTION_L2_128B, CU_TENSOR_MAP_FLOAT_OOB_FILL_NONE);
}
static void make_map3(EncodeFn enc, CUtensorMap* m, const void* ptr, uint64_t cols, uint64_t rows) {
  cuuint64_t dims[3] = {64, rows, cols / 64}, strides[2] = {cols * 2, 128};
  cuuint32_t box[3] = {64, 64, 2}, es[3] = {1, 1, 1};
  enc(m, CU_TENSOR_MAP_DATA_TYPE_BFLOAT16, 3, const_cast<void*>(ptr), dims, strides, box, es, CU_TENSOR_MAP_INTERLEAVE_NONE,
      CU_TENSOR_MAP_SWIZZLE_128B, CU_TENSOR_MAP_L2_PROMOTION_L2_128B, CU_TENSOR_MAP_FLOAT_OOB_FILL_NONE);
}
template <typename T> static void* sym_addr(const T& s) { void* a = nullptr; cudaGetSymbolAddress(&a, s); return a; }

extern "C" void kernel_launch(void* const* d_in, const int* in_sizes, int n_in, void* d_out, int out_size) {
  void* fn = nullptr;
  cudaDriverEntryPointQueryResult qr;
  cudaGetDriverEntryPoint("cuTensorMapEncodeTiled", &fn, cudaEnableDefault, &qr);
  EncodeFn enc = (EncodeFn)fn;
  Params p;
  const CUtensorMapSwizzle S128 = CU_TENSOR_MAP_SWIZZLE_128B, S64 = CU_TENSOR_MAP_SWIZZLE_64B;
  make_map3(enc, &p.wq, d_in[1], DM, DM);
  make_map3(enc, &p.wo, d_in[4], DM, DM);
  make_map3(enc, &p.wd, d_in[8], DM, FF);
  make_map3(enc, &p.wg2, d_in[6], FF, DM);
  make_map3(enc, &p.wu2, d_in[7], FF, DM);
  make_map(enc, &p.wg1, d_in[6], FF, DM, 64, 64, S128);
  make_map(enc, &p.wu1, d_in[7], FF, DM, 64, 64, S128);
  make_map(enc, &p.wk, d_in[2], 32, DM, 32, 256, S64);
  make_map(enc, &p.wv, d_in[3], 32, DM, 32, 256, S64);
  make_map(enc, &p.h1, sym_addr(g_h1), DM, SEQ, 64, 128, S128);
  make_map(enc, &p.ob, sym_addr(g_o), DM, SEQ, 64, 128, S128);
  make_map(enc, &p.h2, sym_addr(g_h2), DM, SEQ, 64, 128, S128);
  make_map(enc, &p.hh, sym_addr(g_hh), FF, SEQ, 64, 128, S128);
  make_map(enc, &p.xm, d_in[0], DM, SEQ, 64, 128, S128);
  make_map(enc, &p.obs, sym_addr(g_o), DM, SEQ, 64, 64, S128);
  make_map(enc, &p.h2s, sym_addr(g_h2), DM, SEQ, 64, 64, S128);
  make_map(enc, &p.hhs, sym_addr(g_hh), FF, SEQ, 64, 64, S128);
  make_map(enc, &p.outs, d_out, DM, SEQ, 64, 64, S128);
  make_map(enc, &p.kb, sym_addr(g_k), 32, SEQ, 32, 128, S64);
  make_map(enc, &p.vt, sym_addr(g_vt), SEQ, 40, 64, 40, S128);
  make_map(enc, &p.wm, d_in[10], MODN, DM, 16, 256, CU_TENSOR_MAP_SWIZZLE_NONE);
  p.x = (const bf16*)d_in[0];
  p.c = (const bf16*)d_in[9];
  p.wmod = (const bf16*)d_in[10];
  cudaFuncSetAttribute(adaln_block_kernel, cudaFuncAttributeMaxDynamicSharedMemorySize, SMEM_BYTES);
  adaln_block_kernel<<<NCTA, NTHREADS, SMEM_BYTES>>>(p);
}
```

```cpp
#include <cuda_runtime.h>
#include <cuda_bf16.h>
#include <cuda.h>
#include <stdint.h>
#include <type_traits>

typedef __nv_bfloat16 bf16;

template<int TA, int TB> __device__ __forceinline__ void wgmma_m64n128k16_ss(float (&d)[64], uint64_t da, uint64_t db, int scale_d) {
  asm volatile("{\n.reg .pred p;\nsetp.ne.b32 p, %66, 0;\n"
    "wgmma.mma_async.sync.aligned.m64n128k16.f32.bf16.bf16 "
    "{%0, %1, %2, %3, %4, %5, %6, %7, %8, %9, %10, %11, %12, %13, %14, %15, %16, %17, %18, %19, %20, %21, %22, %23, %24, %25, %26, %27, %28, %29, %30, %31, %32, %33, %34, %35, %36, %37, %38, %39, %40, %41, %42, %43, %44, %45, %46, %47, %48, %49, %50, %51, %52, %53, %54, %55, %56, %57, %58, %59, %60, %61, %62, %63}, "
    "%64, %65, p, 1, 1, %67, %68;\n}\n"
    : "+f"(d[0]), "+f"(d[1]), "+f"(d[2]), "+f"(d[3]), "+f"(d[4]), "+f"(d[5]), "+f"(d[6]), "+f"(d[7]), "+f"(d[8]), "+f"(d[9]), "+f"(d[10]), "+f"(d[11]), "+f"(d[12]), "+f"(d[13]), "+f"(d[14]), "+f"(d[15]), "+f"(d[16]), "+f"(d[17]), "+f"(d[18]), "+f"(d[19]), "+f"(d[20]), "+f"(d[21]), "+f"(d[22]), "+f"(d[23]), "+f"(d[24]), "+f"(d[25]), "+f"(d[26]), "+f"(d[27]), "+f"(d[28]), "+f"(d[29]), "+f"(d[30]), "+f"(d[31]), "+f"(d[32]), "+f"(d[33]), "+f"(d[34]), "+f"(d[35]), "+f"(d[36]), "+f"(d[37]), "+f"(d[38]), "+f"(d[39]), "+f"(d[40]), "+f"(d[41]), "+f"(d[42]), "+f"(d[43]), "+f"(d[44]), "+f"(d[45]), "+f"(d[46]), "+f"(d[47]), "+f"(d[48]), "+f"(d[49]), "+f"(d[50]), "+f"(d[51]), "+f"(d[52]), "+f"(d[53]), "+f"(d[54]), "+f"(d[55]), "+f"(d[56]), "+f"(d[57]), "+f"(d[58]), "+f"(d[59]), "+f"(d[60]), "+f"(d[61]), "+f"(d[62]), "+f"(d[63])
    : "l"(da), "l"(db), "r"(scale_d), "n"(TA), "n"(TB));
}
template<int TA, int TB> __device__ __forceinline__ void wgmma_m64n256k16_ss(float (&d)[128], uint64_t da, uint64_t db, int scale_d) {
  asm volatile("{\n.reg .pred p;\nsetp.ne.b32 p, %130, 0;\n"
    "wgmma.mma_async.sync.aligned.m64n256k16.f32.bf16.bf16 "
    "{%0, %1, %2, %3, %4, %5, %6, %7, %8, %9, %10, %11, %12, %13, %14, %15, %16, %17, %18, %19, %20, %21, %22, %23, %24, %25, %26, %27, %28, %29, %30, %31, %32, %33, %34, %35, %36, %37, %38, %39, %40, %41, %42, %43, %44, %45, %46, %47, %48, %49, %50, %51, %52, %53, %54, %55, %56, %57, %58, %59, %60, %61, %62, %63, %64, %65, %66, %67, %68, %69, %70, %71, %72, %73, %74, %75, %76, %77, %78, %79, %80, %81, %82, %83, %84, %85, %86, %87, %88, %89, %90, %91, %92, %93, %94, %95, %96, %97, %98, %99, %100, %101, %102, %103, %104, %105, %106, %107, %108, %109, %110, %111, %112, %113, %114, %115, %116, %117, %118, %119, %120, %121, %122, %123, %124, %125, %126, %127}, "
    "%128, %129, p, 1, 1, %131, %132;\n}\n"
    : "+f"(d[0]), "+f"(d[1]), "+f"(d[2]), "+f"(d[3]), "+f"(d[4]), "+f"(d[5]), "+f"(d[6]), "+f"(d[7]), "+f"(d[8]), "+f"(d[9]), "+f"(d[10]), "+f"(d[11]), "+f"(d[12]), "+f"(d[13]), "+f"(d[14]), "+f"(d[15]), "+f"(d[16]), "+f"(d[17]), "+f"(d[18]), "+f"(d[19]), "+f"(d[20]), "+f"(d[21]), "+f"(d[22]), "+f"(d[23]), "+f"(d[24]), "+f"(d[25]), "+f"(d[26]), "+f"(d[27]), "+f"(d[28]), "+f"(d[29]), "+f"(d[30]), "+f"(d[31]), "+f"(d[32]), "+f"(d[33]), "+f"(d[34]), "+f"(d[35]), "+f"(d[36]), "+f"(d[37]), "+f"(d[38]), "+f"(d[39]), "+f"(d[40]), "+f"(d[41]), "+f"(d[42]), "+f"(d[43]), "+f"(d[44]), "+f"(d[45]), "+f"(d[46]), "+f"(d[47]), "+f"(d[48]), "+f"(d[49]), "+f"(d[50]), "+f"(d[51]), "+f"(d[52]), "+f"(d[53]), "+f"(d[54]), "+f"(d[55]), "+f"(d[56]), "+f"(d[57]), "+f"(d[58]), "+f"(d[59]), "+f"(d[60]), "+f"(d[61]), "+f"(d[62]), "+f"(d[63]), "+f"(d[64]), "+f"(d[65]), "+f"(d[66]), "+f"(d[67]), "+f"(d[68]), "+f"(d[69]), "+f"(d[70]), "+f"(d[71]), "+f"(d[72]), "+f"(d[73]), "+f"(d[74]), "+f"(d[75]), "+f"(d[76]), "+f"(d[77]), "+f"(d[78]), "+f"(d[79]), "+f"(d[80]), "+f"(d[81]), "+f"(d[82]), "+f"(d[83]), "+f"(d[84]), "+f"(d[85]), "+f"(d[86]), "+f"(d[87]), "+f"(d[88]), "+f"(d[89]), "+f"(d[90]), "+f"(d[91]), "+f"(d[92]), "+f"(d[93]), "+f"(d[94]), "+f"(d[95]), "+f"(d[96]), "+f"(d[97]), "+f"(d[98]), "+f"(d[99]), "+f"(d[100]), "+f"(d[101]), "+f"(d[102]), "+f"(d[103]), "+f"(d[104]), "+f"(d[105]), "+f"(d[106]), "+f"(d[107]), "+f"(d[108]), "+f"(d[109]), "+f"(d[110]), "+f"(d[111]), "+f"(d[112]), "+f"(d[113]), "+f"(d[114]), "+f"(d[115]), "+f"(d[116]), "+f"(d[117]), "+f"(d[118]), "+f"(d[119]), "+f"(d[120]), "+f"(d[121]), "+f"(d[122]), "+f"(d[123]), "+f"(d[124]), "+f"(d[125]), "+f"(d[126]), "+f"(d[127])
    : "l"(da), "l"(db), "r"(scale_d), "n"(TA), "n"(TB));
}
template<int TA, int TB> __device__ __forceinline__ void wgmma_m64n16k16_ss(float (&d)[8], uint64_t da, uint64_t db, int scale_d) {
  asm volatile("{\n.reg .pred p;\nsetp.ne.b32 p, %10, 0;\n"
    "wgmma.mma_async.sync.aligned.m64n16k16.f32.bf16.bf16 "
    "{%0, %1, %2, %3, %4, %5, %6, %7}, "
    "%8, %9, p, 1, 1, %11, %12;\n}\n"
    : "+f"(d[0]), "+f"(d[1]), "+f"(d[2]), "+f"(d[3]), "+f"(d[4]), "+f"(d[5]), "+f"(d[6]), "+f"(d[7])
    : "l"(da), "l"(db), "r"(scale_d), "n"(TA), "n"(TB));
}
template<int TB> __device__ __forceinline__ void wgmma_m64n64k16_rs(float (&d)[32], uint32_t a0, uint32_t a1, uint32_t a2, uint32_t a3, uint64_t db, int scale_d) {
  asm volatile("{\n.reg .pred p;\nsetp.ne.b32 p, %37, 0;\n"
    "wgmma.mma_async.sync.aligned.m64n64k16.f32.bf16.bf16 "
    "{%0, %1, %2, %3, %4, %5, %6, %7, %8, %9, %10, %11, %12, %13, %14, %15, %16, %17, %18, %19, %20, %21, %22, %23, %24, %25, %26, %27, %28, %29, %30, %31}, "
    "{%32, %33, %34, %35}, %36, p, 1, 1, %38;\n}\n"
    : "+f"(d[0]), "+f"(d[1]), "+f"(d[2]), "+f"(d[3]), "+f"(d[4]), "+f"(d[5]), "+f"(d[6]), "+f"(d[7]), "+f"(d[8]), "+f"(d[9]), "+f"(d[10]), "+f"(d[11]), "+f"(d[12]), "+f"(d[13]), "+f"(d[14]), "+f"(d[15]), "+f"(d[16]), "+f"(d[17]), "+f"(d[18]), "+f"(d[19]), "+f"(d[20]), "+f"(d[21]), "+f"(d[22]), "+f"(d[23]), "+f"(d[24]), "+f"(d[25]), "+f"(d[26]), "+f"(d[27]), "+f"(d[28]), "+f"(d[29]), "+f"(d[30]), "+f"(d[31])
    : "r"(a0), "r"(a1), "r"(a2), "r"(a3), "l"(db), "r"(scale_d), "n"(TB));
}
template<int TB> __device__ __forceinline__ void wgmma_m64n40k16_rs(float (&d)[20], uint32_t a0, uint32_t a1, uint32_t a2, uint32_t a3, uint64_t db, int scale_d) {
  asm volatile("{\n.reg .pred p;\nsetp.ne.b32 p, %25, 0;\n"
    "wgmma.mma_async.sync.aligned.m64n40k16.f32.bf16.bf16 "
    "{%0, %1, %2, %3, %4, %5, %6, %7, %8, %9, %10, %11, %12, %13, %14, %15, %16, %17, %18, %19}, "
    "{%20, %21, %22, %23}, %24, p, 1, 1, %26;\n}\n"
    : "+f"(d[0]), "+f"(d[1]), "+f"(d[2]), "+f"(d[3]), "+f"(d[4]), "+f"(d[5]), "+f"(d[6]), "+f"(d[7]), "+f"(d[8]), "+f"(d[9]), "+f"(d[10]), "+f"(d[11]), "+f"(d[12]), "+f"(d[13]), "+f"(d[14]), "+f"(d[15]), "+f"(d[16]), "+f"(d[17]), "+f"(d[18]), "+f"(d[19])
    : "r"(a0), "r"(a1), "r"(a2), "r"(a3), "l"(db), "r"(scale_d), "n"(TB));
}

constexpr int SEQ = 2048, DM = 1024, FF = 3584, MODN = 6144;
constexpr int NTHREADS = 384, NWORK = 128, NCTA = 132;
constexpr uint32_t SLOT = 16384, NSLOT = 12;
constexpr uint32_t OFF_STG = NSLOT * SLOT;
constexpr uint32_t OFF_FULL = OFF_STG + 32768;
constexpr uint32_t OFF_EMPTY = OFF_FULL + 8 * NSLOT;
constexpr uint32_t OFF_STF = OFF_EMPTY + 8 * NSLOT;
constexpr uint32_t OFF_STE = OFF_STF + 16;
constexpr uint32_t OFF_AUX = OFF_STE + 16;
constexpr uint32_t OFF_VEC = OFF_FULL + 272;
constexpr uint32_t SMEM_BYTES = OFF_VEC + 2048 + 512;
static_assert(SMEM_BYTES <= 232448, "shared memory budget");

constexpr int F_MOD2 = 0, F_H1 = 1, F_KV = 17, F_O = 33, F_H2 = 65, F_HH = 81, F_EPOCH = 113, F_COUNT = 114;

constexpr uint32_t ORD_Q = 0x321054;
constexpr uint32_t ORD_A = 0x1032;
constexpr uint32_t ORD_O = 0x10324;
constexpr uint32_t ORD_G = 0x3210;
constexpr uint32_t ORD_D = 0x543210;

constexpr int NPOLY = 3;

__device__ float g_mod[MODN];
__device__ __align__(1024) bf16 g_h1[SEQ * DM];
__device__ __align__(1024) bf16 g_k[SEQ * 32];
__device__ __align__(1024) bf16 g_vt[40 * SEQ];
__device__ __align__(1024) bf16 g_o[SEQ * DM];
__device__ __align__(1024) bf16 g_h2[SEQ * DM];
__device__ __align__(1024) bf16 g_hh[SEQ * FF];
__device__ __align__(16) uint32_t g_mod1[DM];
__device__ __align__(16) uint2 g_stats[16 * 8 * 128];
__device__ uint32_t g_flags[F_COUNT * 32];

struct Params {
  CUtensorMap wq, wo, wd, wg2, wu2;
  CUtensorMap wg1, wu1;
  CUtensorMap wk, wv;
  CUtensorMap h1, ob, h2, hh, xm;
  CUtensorMap obs, h2s, hhs, outs;
  CUtensorMap kb, vt;
  CUtensorMap wm;
  const bf16* x;
  const bf16* c;
  const bf16* wmod;
};

template <int V> struct IC { static constexpr int value = V; __host__ __device__ constexpr operator int() const { return V; } };
template <int I, int N, typename F> __device__ __forceinline__ void static_for(F&& f) {
  if constexpr (I < N) { f(IC<I>{}); static_for<I + 1, N>(f); }
}
__device__ __forceinline__ uint32_t opaque(uint32_t x) { uint32_t r; asm volatile("mov.u32 %0, %1;" : "=r"(r) : "r"(x)); return r; }
__device__ __forceinline__ void mbar_init(uint32_t bar, uint32_t cnt) { asm volatile("mbarrier.init.shared::cta.b64 [%0], %1;" ::"r"(bar), "r"(cnt)); }
__device__ __forceinline__ void mbar_expect_tx(uint32_t bar, uint32_t bytes) { asm volatile("mbarrier.arrive.expect_tx.shared::cta.b64 _, [%0], %1;" ::"r"(bar), "r"(bytes) : "memory"); }
__device__ __forceinline__ void mbar_arrive(uint32_t bar) { asm volatile("mbarrier.arrive.shared::cta.b64 _, [%0];" ::"r"(bar) : "memory"); }
__device__ __forceinline__ bool mbar_try(uint32_t bar, uint32_t parity) {
  uint32_t ok;
  asm volatile("{\n.reg .pred p;\nmbarrier.try_wait.parity.shared::cta.b64 p, [%1], %2;\nselp.u32 %0,1,0,p;\n}" : "=r"(ok) : "r"(bar), "r"(parity) : "memory");
  return ok;
}
__device__ __forceinline__ void mbar_wait(uint32_t bar, uint32_t parity) {
  asm volatile("{\n.reg .pred p;\n.reg .u32 n;\nmov.u32 n, 0;\n"
               "WAIT_LOOP:\nmbarrier.try_wait.parity.shared::cta.b64 p, [%0], %1;\n@p bra WAIT_DONE;\n"
               "add.u32 n, n, 1;\nsetp.lt.u32 p, n, 16777216;\n@p bra WAIT_LOOP;\ntrap;\nWAIT_DONE:\n}"
               ::"r"(bar), "r"(parity) : "memory");
}
__device__ __forceinline__ void mbar_wait_idle(uint32_t bar, uint32_t parity) {
#pragma unroll 1
  for (int i = 0; i < (1 << 24); i++) { if (mbar_try(bar, parity)) return; __nanosleep(30); }
  __trap();
}

__device__ __forceinline__ void tma_load(uint32_t dst, const CUtensorMap* m, uint32_t bar, int c0, int c1) {
  asm volatile("cp.async.bulk.tensor.2d.shared::cluster.global.mbarrier::complete_tx::bytes [%0], [%1, {%3, %4}], [%2];"
               ::"r"(dst), "l"(m), "r"(bar), "r"(c0), "r"(c1) : "memory");
}
__device__ __forceinline__ void tma_load3(uint32_t dst, const CUtensorMap* m, uint32_t bar, int c0, int c1, int c2) {
  asm volatile("cp.async.bulk.tensor.3d.shared::cluster.global.mbarrier::complete_tx::bytes [%0], [%1, {%3, %4, %5}], [%2];"
               ::"r"(dst), "l"(m), "r"(bar), "r"(c0), "r"(c1), "r"(c2) : "memory");
}
constexpr uint64_t EVICT_FIRST = 0x12F0000000000000ull;
__device__ __forceinline__ void tma_load_s(uint32_t dst, const CUtensorMap* m, uint32_t bar, int c0, int c1, uint64_t pol) {
  asm volatile("cp.async.bulk.tensor.2d.shared::cluster.global.mbarrier::complete_tx::bytes.L2::cache_hint [%0], [%1, {%3, %4}], [%2], %5;"
               ::"r"(dst), "l"(m), "r"(bar), "r"(c0), "r"(c1), "l"(pol) : "memory");
}
__device__ __forceinline__ void tma_load3_s(uint32_t dst, const CUtensorMap* m, uint32_t bar, int c0, int c1, int c2, uint64_t pol) {
  asm volatile("cp.async.bulk.tensor.3d.shared::cluster.global.mbarrier::complete_tx::bytes.L2::cache_hint [%0], [%1, {%3, %4, %5}], [%2], %6;"
               ::"r"(dst), "l"(m), "r"(bar), "r"(c0), "r"(c1), "r"(c2), "l"(pol) : "memory");
}
__device__ __forceinline__ bool elect_one() {
  uint32_t p;
  asm volatile("{\n.reg .pred P;\nelect.sync _|P, 0xffffffff;\nselp.u32 %0,1,0,P;\n}" : "=r"(p));
  return p;
}
__device__ __forceinline__ void tma_store(const CUtensorMap* m, uint32_t src, int c0, int c1) {
  asm volatile("cp.async.bulk.tensor.2d.global.shared::cta.bulk_group [%0, {%2, %3}], [%1];" ::"l"(m), "r"(src), "r"(c0), "r"(c1) : "memory");
}
__device__ __forceinline__ void tma_prefetch3(const CUtensorMap* m, int c0, int c1, int c2) {
  asm volatile("cp.async.bulk.prefetch.tensor.3d.L2.global [%0, {%1, %2, %3}];" ::"l"(m), "r"(c0), "r"(c1), "r"(c2) : "memory");
}
__device__ __forceinline__ void bulk_commit() { asm volatile("cp.async.bulk.commit_group;" ::: "memory"); }
__device__ __forceinline__ void bulk_wait_read() { asm volatile("cp.async.bulk.wait_group.read 0;" ::: "memory"); }
__device__ __forceinline__ void bulk_wait_all() { asm volatile("cp.async.bulk.wait_group 0;" ::: "memory"); }
__device__ __forceinline__ void fence_async_smem() { asm volatile("fence.proxy.async.shared::cta;" ::: "memory"); }
__device__ __forceinline__ void fence_async_global() { asm volatile("fence.proxy.async.global;" ::: "memory"); }
__device__ __forceinline__ void wg_fence() { asm volatile("wgmma.fence.sync.aligned;" ::: "memory"); }
__device__ __forceinline__ void wg_commit() { asm volatile("wgmma.commit_group.sync.aligned;" ::: "memory"); }
template <int N> __device__ __forceinline__ void wg_wait() { asm volatile("wgmma.wait_group.sync.aligned %0;" ::"n"(N) : "memory"); }
template <int R> __device__ __forceinline__ void reg_alloc() { asm volatile("setmaxnreg.inc.sync.aligned.u32 %0;" ::"n"(R)); }
template <int R> __device__ __forceinline__ void reg_dealloc() { asm volatile("setmaxnreg.dec.sync.aligned.u32 %0;" ::"n"(R)); }
__device__ __forceinline__ void bar_sync(int id, int n) { asm volatile("bar.sync %0, %1;" ::"r"(id), "r"(n) : "memory"); }
__device__ __forceinline__ uint64_t dsc(uint32_t lo, uint32_t hi) { uint64_t r; asm("mov.b64 %0, {%1,%2};" : "=l"(r) : "r"(lo), "r"(hi)); return r; }
constexpr uint32_t HI_128 = (1024 >> 4) | (1u << 30);
constexpr uint32_t HI_64 = (512 >> 4) | (2u << 30);

template <int N> __device__ __forceinline__ void fence_regs(float (&r)[N]) {
#pragma unroll
  for (int i = 0; i < N; i++) asm volatile("" : "+f"(r[i])::"memory");
}
template <int N> __device__ __forceinline__ void fence_regs(uint32_t (&r)[N]) {
#pragma unroll
  for (int i = 0; i < N; i++) asm volatile("" : "+r"(r[i])::"memory");
}
__device__ __forceinline__ void fence4(uint32_t* p) { asm volatile("" : "+r"(p[0]), "+r"(p[1]), "+r"(p[2]), "+r"(p[3])::"memory"); }

__device__ __forceinline__ uint32_t* flag_ptr(int i) { return g_flags + i * 32; }
__device__ __forceinline__ void flag_signal(int i) {
  asm volatile("fence.acq_rel.gpu;\nred.relaxed.gpu.global.add.u32 [%0], 1;" ::"l"(flag_ptr(i)) : "memory");
}
__device__ __forceinline__ uint32_t load_epoch() {
  uint32_t v;
  asm volatile("ld.relaxed.gpu.global.u32 %0, [%1];" : "=r"(v) : "l"(flag_ptr(F_EPOCH)) : "memory");
  return v + 1;
}
template <int SLEEP_NS = 100>
__device__ __forceinline__ void flag_wait(int i, uint32_t target) {
  const uint32_t* p = flag_ptr(i);
#pragma unroll 1
  for (int it = 0; it < (1 << 22); it++) {
    uint32_t v;
    asm volatile("ld.acquire.gpu.global.u32 %0, [%1];" : "=r"(v) : "l"(p) : "memory");
    if ((int32_t)(v - target) >= 0) return;
    __nanosleep(SLEEP_NS);
  }
  __trap();
}

__device__ __forceinline__ void st_tagged2(uint2* p, float a, float b) {
  asm volatile("st.relaxed.gpu.global.v2.u32 [%0], {%1,%2};" ::"l"(p), "r"(__float_as_uint(a) | 1u), "r"(__float_as_uint(b) | 1u) : "memory");
}
__device__ __forceinline__ uint4 ld_bf16x8_valid(const uint32_t* p) {
  uint4 v;
#pragma unroll 1
  for (int it = 0; it < (1 << 22); it++) {
    asm volatile("ld.relaxed.gpu.global.v4.u32 {%0,%1,%2,%3}, [%4];" : "=r"(v.x), "=r"(v.y), "=r"(v.z), "=r"(v.w) : "l"(p) : "memory");
    if (!(__vcmpeq2(v.x, 0u) | __vcmpeq2(v.y, 0u) | __vcmpeq2(v.z, 0u) | __vcmpeq2(v.w, 0u))) return make_uint4(~v.x, ~v.y, ~v.z, ~v.w);
    __nanosleep(100);
  }
  __trap();
  return v;
}
__device__ __forceinline__ void ld_tagged2x4(const uint2* p0, const uint2* p1, const uint2* p2, const uint2* p3, uint2 (&v)[4]) {
#pragma unroll 1
  for (int it = 0; it < (1 << 22); it++) {
    asm volatile("ld.relaxed.gpu.global.v2.u32 {%0,%1}, [%8];\nld.relaxed.gpu.global.v2.u32 {%2,%3}, [%9];\n"
                 "ld.relaxed.gpu.global.v2.u32 {%4,%5}, [%10];\nld.relaxed.gpu.global.v2.u32 {%6,%7}, [%11];"
                 : "=r"(v[0].x), "=r"(v[0].y), "=r"(v[1].x), "=r"(v[1].y), "=r"(v[2].x), "=r"(v[2].y), "=r"(v[3].x), "=r"(v[3].y)
                 : "l"(p0), "l"(p1), "l"(p2), "l"(p3) : "memory");
    if (v[0].x & v[0].y & v[1].x & v[1].y & v[2].x & v[2].y & v[3].x & v[3].y & 1u) return;
  }
  __trap();
}
__device__ __forceinline__ float ex2(float x) { float y; asm("ex2.approx.ftz.f32 %0, %1;" : "=f"(y) : "f"(x)); return y; }
__device__ __forceinline__ float tanh_fast(float x) { float y; asm("tanh.approx.f32 %0, %1;" : "=f"(y) : "f"(x)); return y; }
__device__ __forceinline__ uint32_t pack_bf16(float lo, float hi) { uint32_t r; asm("cvt.rn.bf16x2.f32 %0, %1, %2;" : "=r"(r) : "f"(hi), "f"(lo)); return r; }
__device__ __forceinline__ float bf_lo(uint32_t v) { return __uint_as_float(v << 16); }
__device__ __forceinline__ float bf_hi(uint32_t v) { return __uint_as_float(v & 0xffff0000u); }
__device__ __forceinline__ float round_bf16(float x) { return bf_lo(pack_bf16(x, 0.f)); }
__device__ __forceinline__ float fma_sat(float a, float b, float c) { float r; asm("fma.rn.sat.f32 %0, %1, %2, %3;" : "=f"(r) : "f"(a), "f"(b), "f"(c)); return r; }
__device__ __forceinline__ void stsm4(uint32_t addr, uint32_t a, uint32_t b, uint32_t c, uint32_t d) {
  asm volatile("stmatrix.sync.aligned.m8n8.x4.shared.b16 [%0], {%1,%2,%3,%4};" ::"r"(addr), "r"(a), "r"(b), "r"(c), "r"(d) : "memory");
}
__device__ __forceinline__ void ldsm4(uint32_t addr, uint32_t& a, uint32_t& b, uint32_t& c, uint32_t& d) {
  asm volatile("ldmatrix.sync.aligned.m8n8.x4.shared.b16 {%0,%1,%2,%3}, [%4];" : "=r"(a), "=r"(b), "=r"(c), "=r"(d) : "r"(addr));
}
__device__ __forceinline__ float lds32(uint32_t a) { float v; asm volatile("ld.shared.f32 %0, [%1];" : "=f"(v) : "r"(a)); return v; }
__device__ __forceinline__ float2 lds64(uint32_t a) { float2 v; asm volatile("ld.shared.v2.f32 {%0,%1}, [%2];" : "=f"(v.x), "=f"(v.y) : "r"(a)); return v; }
__device__ __forceinline__ void sts32(uint32_t a, float v) { asm volatile("st.shared.f32 [%0], %1;" ::"r"(a), "f"(v) : "memory"); }
__device__ __forceinline__ void sts128(uint32_t a, uint4 v) { asm volatile("st.shared.v4.b32 [%0], {%1,%2,%3,%4};" ::"r"(a), "r"(v.x), "r"(v.y), "r"(v.z), "r"(v.w) : "memory"); }


struct Producer {
  uint32_t sb, emask;
  template <int BAR> __device__ __forceinline__ void acquire() {
    mbar_wait(sb + OFF_EMPTY + 8 * BAR, (emask >> BAR) & 1);
    emask ^= 1u << BAR;
  }
  template <int S0> __device__ __forceinline__ void arm(uint32_t bytes) { mbar_expect_tx(sb + OFF_FULL + 8 * S0, bytes); }
  template <int S0> __device__ __forceinline__ void begin(uint32_t bytes) { acquire<S0>(); arm<S0>(bytes); }
  template <int S0> __device__ __forceinline__ void loadA(const CUtensorMap* m, int k0, int row0) {
    tma_load(sb + S0 * SLOT, m, sb + OFF_FULL + 8 * S0, k0, row0);
  }
  template <int S0> __device__ __forceinline__ void loadB(const CUtensorMap* m, int nblk, int k0) {
    tma_load3_s(sb + (S0 + 1) * SLOT, m, sb + OFF_FULL + 8 * S0, 0, k0, nblk, EVICT_FIRST);
  }
};
__host__ __device__ constexpr int ord(uint32_t o, int i) { return (o >> (4 * i)) & 15; }

__device__ __forceinline__ void producer_role(const Params& p, uint32_t sb, int mt, int j, int cta) {
  Producer P{sb, 0xFFFu};
  const uint32_t ep = load_epoch();
  auto wait_and_fence = [&](int flag, uint32_t n) { flag_wait(flag, n * ep); fence_async_global(); };
  const int row0 = mt * 128;
  static_for<0, 4>([&](auto Q) {
    constexpr int q = decltype(Q)::value;
    P.begin<2 * q>(32768);
    tma_load(sb + 2 * q * SLOT, &p.wk, sb + OFF_FULL + 16 * q, 0, 256 * q);
    tma_load(sb + (2 * q + 1) * SLOT, &p.wv, sb + OFF_FULL + 16 * q, 0, 256 * q);
  });
  tma_prefetch3(&p.wq, 0, mt * 64, j * 2);
  mbar_wait(sb + OFF_AUX + 32, 0);
  static_for<0, 2>([&](auto I) { constexpr int s = 2 * ord(ORD_Q, I); P.begin<s>(32768); P.loadB<s>(&p.wq, j * 2, I * 64); });
  wait_and_fence(F_H1 + mt, 8);
  static_for<0, 2>([&](auto I) { P.loadA<2 * ord(ORD_Q, I)>(&p.h1, I * 64, row0); });
  static_for<2, 16>([&](auto I) {
    constexpr int s = 2 * ord(ORD_Q, I % 6);
    P.begin<s>(32768); P.loadB<s>(&p.wq, j * 2, I * 64); P.loadA<s>(&p.h1, I * 64, row0);
  });
#pragma unroll 1
  for (int r = 0; r < 16; r++) {
    static_for<0, 4>([&](auto Q) {
      constexpr int s = 2 * ord(ORD_A, Q);
      const int t = (4 * r + Q) & 15;
      P.begin<s>(8192 + 2 * 5120);
      if (r < 4) wait_and_fence(F_KV + t, 8);
      const uint32_t fb = sb + OFF_FULL + 8 * s, d = sb + s * SLOT;
      tma_load(d, &p.kb, fb, 0, t * 128);
      tma_load(d + 8192, &p.vt, fb, t * 128, 0);
      tma_load(d + 13312, &p.vt, fb, t * 128 + 64, 0);
    });
    if (r == 13) {
      P.begin<10>(32768);
      tma_load(sb + 10 * SLOT, &p.xm, sb + OFF_FULL + 80, j * 128, row0);
      tma_load(sb + 11 * SLOT, &p.xm, sb + OFF_FULL + 80, j * 128 + 64, row0);
      constexpr int so = 2 * ord(ORD_O, 0);
      P.begin<so>(16384); P.loadB<so>(&p.wo, j * 2, j * 128);
    }
  }
  { constexpr int s = 2 * ord(ORD_O, 1); P.begin<s>(16384); P.loadB<s>(&p.wo, j * 2, j * 128 + 64); }
  wait_and_fence(F_O + 2 * mt, 8);
  static_for<2, 9>([&](auto I) {
    constexpr int s = 2 * ord(ORD_O, I % 5);
    const int k0 = 128 * ((I - 2) + ((I - 2) >= j));
    P.begin<s>(32768); P.loadB<s>(&p.wo, j * 2, k0); P.loadA<s>(&p.ob, k0, row0);
  });
  static_for<9, 11>([&](auto I) {
    constexpr int s = 2 * ord(ORD_O, I % 5);
    P.begin<s>(32768); P.loadB<s>(&p.wo, j * 2, 128 * ((I - 9) + ((I - 9) >= j)) + 64);
  });
  wait_and_fence(F_O + 2 * mt + 1, 8);
  static_for<9, 11>([&](auto I) { P.loadA<2 * ord(ORD_O, I % 5)>(&p.ob, 128 * ((I - 9) + ((I - 9) >= j)) + 64, row0); });
  static_for<11, 16>([&](auto I) {
    constexpr int s = 2 * ord(ORD_O, I % 5);
    const int k0 = 128 * ((I - 9) + ((I - 9) >= j)) + 64;
    P.begin<s>(32768); P.loadB<s>(&p.wo, j * 2, k0); P.loadA<s>(&p.ob, k0, row0);
  });
  auto gu_b = [&](auto Q, int t, int k0, uint32_t abytes) {
    constexpr int s = 3 * Q;
    const uint32_t fb = sb + OFF_FULL + 8 * s, d = sb + (s + 1) * SLOT;
    P.arm<s>(32768 + abytes);
    tma_load3_s(d, &p.wg2, fb, 0, k0, j * 7 + t * 2, EVICT_FIRST);
    tma_load3_s(d + 16384, &p.wu2, fb, 0, k0, j * 7 + t * 2, EVICT_FIRST);
  };
  using I0 = IC<0>; using I1 = IC<1>; using I2 = IC<2>; using I3 = IC<3>;
  auto gk0 = [&](int i) { const int o = (i - 2) >> 1; return i < 2 ? 2 * j + i : 2 * (o + (o >= j)) + (i & 1); };
  P.acquire<0>(); P.acquire<2>(); gu_b(I0{}, 0, gk0(0) * 64, 0);
  P.acquire<4>(); P.emask &= ~(1u << 3); gu_b(I1{}, 0, gk0(1) * 64, 0);
  P.acquire<6>(); P.acquire<8>(); gu_b(I2{}, 0, gk0(2) * 64, 16384);
  P.acquire<10>(); P.emask &= ~(1u << 9); gu_b(I3{}, 0, gk0(3) * 64, 16384);
  wait_and_fence(F_H2 + mt, 8);
  P.loadA<6>(&p.h2, gk0(2) * 64, row0); P.loadA<9>(&p.h2, gk0(3) * 64, row0);
#pragma unroll 1
  for (int r = 1; r < 12; r++) {
    const int t = r >> 2;
    static_for<0, 4>([&](auto Q) {
      const int i = ((r & 3) << 2) + Q, kb = r < 4 ? gk0(i) : i;
      P.acquire<3 * Q>();
      gu_b(Q, t, kb * 64, 16384);
      P.loadA<3 * Q>(&p.h2, kb * 64, row0);
    });
  }
  auto g3 = [&](auto S, int k0) {
    constexpr int s = decltype(S)::value;
    const uint32_t fb = sb + OFF_FULL + 8 * s, d = sb + (s + 1) * SLOT;
    P.arm<s>(32768);
    tma_load_s(d, &p.wg1, fb, (j * 7 + 6) * 64, k0, EVICT_FIRST); tma_load_s(d + 8192, &p.wu1, fb, (j * 7 + 6) * 64, k0, EVICT_FIRST);
    P.loadA<s>(&p.h2, k0, row0);
  };
  P.acquire<0>(); g3(IC<0>{}, 0);
  P.acquire<3>(); g3(IC<2>{}, 64);
  g3(IC<4>{}, 128);
  P.acquire<6>(); g3(IC<6>{}, 192);
  P.acquire<9>(); g3(IC<8>{}, 256);
  g3(IC<10>{}, 320);
  static_for<6, 16>([&](auto M) { constexpr int s = 2 * (M % 6); P.acquire<s>(); g3(IC<s>{}, 64 * M); });
  auto dkb = [&](int i) { return i < 48 ? 7 * ((i & 15) >> 1) + 2 * (i >> 4) + (i & 1) : 7 * (i - 48) + 6; };
  { P.begin<8>(32768); P.loadB<8>(&p.wd, j * 2, dkb(0) * 64); }
  { P.begin<10>(32768); P.loadB<10>(&p.wd, j * 2, dkb(1) * 64); }
  wait_and_fence(F_HH + 2 * mt, 8);
  P.loadA<8>(&p.hh, dkb(0) * 64, row0); P.loadA<10>(&p.hh, dkb(1) * 64, row0);
#pragma unroll 1
  for (int r = 0; r < 7; r++)
    static_for<0, 6>([&](auto Q) {
      const int k0 = dkb(2 + 6 * r + Q) * 64;
      P.begin<2 * Q>(32768); P.loadB<2 * Q>(&p.wd, j * 2, k0); P.loadA<2 * Q>(&p.hh, k0, row0);
    });
  static_for<0, 4>([&](auto Q) {
    const int k0 = dkb(44 + Q) * 64;
    P.begin<2 * Q>(32768); P.loadB<2 * Q>(&p.wd, j * 2, k0); P.loadA<2 * Q>(&p.hh, k0, row0);
  });
  static_for<4, 6>([&](auto Q) { P.begin<2 * Q>(32768); P.loadB<2 * Q>(&p.wd, j * 2, (7 * (Q - 4) + 6) * 64); });
  wait_and_fence(F_HH + 2 * mt + 1, 8);
  static_for<4, 6>([&](auto Q) { P.loadA<2 * Q>(&p.hh, (7 * (Q - 4) + 6) * 64, row0); });
  static_for<0, 6>([&](auto Q) {
    P.begin<2 * Q>(32768); P.loadB<2 * Q>(&p.wd, j * 2, (7 * (Q + 2) + 6) * 64); P.loadA<2 * Q>(&p.hh, (7 * (Q + 2) + 6) * 64, row0);
  });
}

__device__ __forceinline__ void store_role(const Params& p, uint32_t sb, int mt, int j) {
  uint32_t ph = 0;
  auto job = [&](const CUtensorMap* m, int col, int box0, int nbox, bool rel, int flag) {
    for (int w = 0; w < 2; w++) {
      mbar_wait_idle(sb + OFF_STF + 8 * w, ph);
      for (int b = 0; b < nbox; b++) tma_store(m, sb + OFF_STG + w * 16384 + (box0 + b) * 8192, col + b * 64, mt * 128 + w * 64);
    }
    ph ^= 1;
    bulk_commit();
    if (rel) { bulk_wait_read(); mbar_arrive(sb + OFF_STE); mbar_arrive(sb + OFF_STE + 8); }
    if (flag >= 0) { bulk_wait_all(); flag_signal(flag); }
  };
  job(&p.obs, j * 128, 0, 1, false, F_O + 2 * mt);
  job(&p.obs, j * 128 + 64, 1, 1, true, F_O + 2 * mt + 1);
  job(&p.h2s, j * 128, 0, 2, true, F_H2 + mt);
  job(&p.hhs, j * 448, 0, 2, true, -1);
  job(&p.hhs, j * 448 + 128, 0, 2, true, -1);
  job(&p.hhs, j * 448 + 256, 0, 2, true, F_HH + 2 * mt);
  job(&p.hhs, j * 448 + 384, 0, 1, true, F_HH + 2 * mt + 1);
  job(&p.outs, j * 128, 0, 2, false, -1);
  bulk_wait_read();
}

__device__ __forceinline__ void signal_role(uint32_t sb, int mt, int j) {
  const int lane = threadIdx.x & 31;
  if (elect_one()) {
    const uint32_t ep = load_epoch();
    mbar_wait(sb + OFF_AUX + 16, 0);
    flag_signal(F_H1 + mt);
    mbar_wait(sb + OFF_AUX + 24, 0);
    flag_signal(F_KV + mt);
    flag_wait<1000>(F_MOD2, (NCTA - NWORK) * ep);
  }
  __syncwarp();
#pragma unroll
  for (int v = 0; v < 4; v++) {
    float4 m = __ldcg(reinterpret_cast<const float4*>(g_mod + (v + 2) * DM + j * 128) + lane);
    if (v == 2) { m.x += 1.f; m.y += 1.f; m.z += 1.f; m.w += 1.f; }
    sts128(sb + OFF_VEC + v * 512 + lane * 16, make_uint4(__float_as_uint(m.x), __float_as_uint(m.y), __float_as_uint(m.z), __float_as_uint(m.w)));
  }
  __syncwarp();
  if (lane == 0) mbar_arrive(sb + OFF_AUX + 8);
}

struct Cons {
  uint32_t sb, fmask, stph;
  int cw, lane, warp;
  bool leader;
  __device__ __forceinline__ void wait_full(int slot) {
    mbar_wait(sb + OFF_FULL + 8 * slot, (fmask >> slot) & 1);
    fmask ^= 1u << slot;
  }
  __device__ __forceinline__ void release(int s0) { if (lane == 0) mbar_arrive(sb + OFF_EMPTY + 8 * s0); }
  __device__ __forceinline__ void stg_acquire() { mbar_wait(sb + OFF_STE + 8 * cw, stph); stph ^= 1; }
  __device__ __forceinline__ void stg_publish() {
    fence_async_smem();
    __syncwarp();
    if (lane == 0) mbar_arrive(sb + OFF_STF + 8 * cw);
  }
  __device__ __forceinline__ uint32_t stg_addr(int cb16) const {
    int row = warp * 16 + (lane & 7) + ((lane >> 3) & 1) * 8;
    int chunk = (cb16 & 3) * 2 + (lane >> 4);
    return sb + OFF_STG + cw * 16384 + (cb16 >> 2) * 8192 + row * 128 + ((chunk ^ (row & 7)) << 4);
  }
};

template <int N, int SPS, uint32_t ORD, int NORD>
__device__ __forceinline__ void gemm_loop(Cons& c, float (&acc)[N / 2], int nst, int nown, int idx0 = 0) {
  const uint32_t abase = ((c.sb + c.cw * 8192) >> 4) | (1u << 16);
  const uint32_t bbase = ((c.sb + SLOT) >> 4) | ((8192u >> 4) << 16);
  const uint32_t aown = ((c.sb + OFF_STG + c.cw * 16384) >> 4) | (1u << 16);
  int idx = idx0, prev = 0;
#pragma unroll 1
  for (int i = 0; i < nst; i++) {
    const int s = SPS * ((ORD >> (4 * idx)) & 15);
    c.wait_full(s);
    const uint32_t alo = i < nown ? aown + i * 512 : abase + s * (SLOT >> 4);
    wg_fence();
#pragma unroll
    for (int k = 0; k < 4; k++) {
      const uint64_t da = dsc(alo + k * 2, HI_128), db = dsc(bbase + s * (SLOT >> 4) + k * 128, HI_128);
      if constexpr (N == 256) wgmma_m64n256k16_ss<0, 1>(acc, da, db, (i | k) != 0);
      else wgmma_m64n128k16_ss<0, 1>(acc, da, db, (i | k) != 0);
    }
    wg_commit();
    if (i > 0) { wg_wait<1>(); c.release(prev); }
    prev = s;
    if (++idx == NORD) idx = 0;
  }
  wg_wait<0>();
  c.release(prev);
  fence_regs(acc);
}

__device__ __forceinline__ float exp2_fma(float s, float a, float b) {
  const float MAGIC = 12582912.f - 125.f;
  float y = fma_sat(s, a, b);
  float t = fmaf(y, 253.f, MAGIC);
  float u = t - MAGIC;
  float f = fmaf(y, 253.f, -u);
  float q = fmaf(f, 0.0551716685295105f, 0.2426111251115799f);
  q = fmaf(q, f, 0.6932609677314758f);
  q = fmaf(q, f, 0.9999280571937561f);
  return __uint_as_float(__float_as_uint(q) + (__float_as_uint(t) << 23));
}
constexpr float SM_C = 0.17677669529663687f * 1.4426950408889634f;
struct SoftmaxRow { float mc0, mc1, a, b0, b1; };
template <int G>
__device__ __forceinline__ void softmax_grp(const float (&S)[32], uint32_t (&P)[16], const SoftmaxRow& r) {
  float e[8];
#pragma unroll
  for (int k = 0; k < 8; k++) {
    const bool poly = (G & 1) ? k < NPOLY / 2 : k < (NPOLY + 1) / 2;
    const bool hi = (k >> 1) & 1;
    e[k] = poly ? exp2_fma(S[8 * G + k], r.a, hi ? r.b1 : r.b0) : ex2(fmaf(S[8 * G + k], SM_C, -(hi ? r.mc1 : r.mc0)));
  }
#pragma unroll
  for (int k = 0; k < 4; k++) P[4 * G + k] = pack_bf16(e[2 * k], e[2 * k + 1]);
}

__device__ __forceinline__ void hmma(float (&d)[4], const uint32_t* a, uint32_t b0, uint32_t b1) {
  asm volatile("mma.sync.aligned.m16n8k16.row.col.f32.bf16.bf16.f32 {%0,%1,%2,%3},{%4,%5,%6,%7},{%8,%9},{%0,%1,%2,%3};"
               : "+f"(d[0]), "+f"(d[1]), "+f"(d[2]), "+f"(d[3]) : "r"(a[0]), "r"(a[1]), "r"(a[2]), "r"(a[3]), "r"(b0), "r"(b1));
}
__device__ __forceinline__ void attention_exact(const uint32_t (&q)[8], float (&o16)[20], float& lo0, float& lo1, int lane) {
  float O[4][4] = {}, m0 = -INFINITY, m1 = -INFINITY, l0 = 0.f, l1 = 0.f;
  const uint32_t* K = reinterpret_cast<const uint32_t*>(g_k);
  const uint32_t* V = reinterpret_cast<const uint32_t*>(g_vt);
  const int g = lane >> 2, t = lane & 3;
#pragma unroll 1
  for (int k0 = 0; k0 < SEQ; k0 += 16) {
    float s[2][4] = {};
#pragma unroll
    for (int nb = 0; nb < 2; nb++)
#pragma unroll
      for (int kk = 0; kk < 2; kk++) {
        const uint32_t* kp = K + (k0 + nb * 8 + g) * 16 + kk * 8 + t;
        hmma(s[nb], &q[4 * kk], __ldcg(kp), __ldcg(kp + 4));
      }
    float n0 = fmaxf(fmaxf(s[0][0], s[0][1]), fmaxf(s[1][0], s[1][1])), n1 = fmaxf(fmaxf(s[0][2], s[0][3]), fmaxf(s[1][2], s[1][3]));
    n0 = fmaxf(n0, __shfl_xor_sync(~0u, n0, 1)); n0 = fmaxf(n0, __shfl_xor_sync(~0u, n0, 2));
    n1 = fmaxf(n1, __shfl_xor_sync(~0u, n1, 1)); n1 = fmaxf(n1, __shfl_xor_sync(~0u, n1, 2));
    n0 = fmaxf(n0, m0); n1 = fmaxf(n1, m1);
    const float r0 = exp2f((m0 - n0) * SM_C), r1 = exp2f((m1 - n1) * SM_C);
    m0 = n0; m1 = n1;
    uint32_t pa[4];
#pragma unroll
    for (int nb = 0; nb < 2; nb++) {
      pa[2 * nb] = pack_bf16(exp2f((s[nb][0] - m0) * SM_C), exp2f((s[nb][1] - m0) * SM_C));
      pa[2 * nb + 1] = pack_bf16(exp2f((s[nb][2] - m1) * SM_C), exp2f((s[nb][3] - m1) * SM_C));
    }
    l0 = l0 * r0 + bf_lo(pa[0]) + bf_hi(pa[0]) + bf_lo(pa[2]) + bf_hi(pa[2]);
    l1 = l1 * r1 + bf_lo(pa[1]) + bf_hi(pa[1]) + bf_lo(pa[3]) + bf_hi(pa[3]);
#pragma unroll
    for (int nb = 0; nb < 4; nb++) {
      O[nb][0] *= r0; O[nb][1] *= r0; O[nb][2] *= r1; O[nb][3] *= r1;
      const uint32_t* vp = V + ((nb * 8 + g) * SEQ + k0) / 2 + t;
      hmma(O[nb], pa, __ldcg(vp), __ldcg(vp + 4));
    }
  }
  l0 += __shfl_xor_sync(~0u, l0, 1); l0 += __shfl_xor_sync(~0u, l0, 2);
  l1 += __shfl_xor_sync(~0u, l1, 1); l1 += __shfl_xor_sync(~0u, l1, 2);
#pragma unroll
  for (int nb = 0; nb < 4; nb++)
#pragma unroll
    for (int e = 0; e < 4; e++) o16[4 * nb + e] = O[nb][e];
  lo0 = l0; lo1 = l1;
}

__device__ __forceinline__ SoftmaxRow softmax_offsets(const float (&S)[32]) {
  float m0 = fmaxf(S[0], S[1]), m1 = fmaxf(S[2], S[3]);
#pragma unroll
  for (int i = 1; i < 8; i++) { m0 = fmaxf(m0, fmaxf(S[4 * i], S[4 * i + 1])); m1 = fmaxf(m1, fmaxf(S[4 * i + 2], S[4 * i + 3])); }
  m0 = fmaxf(m0, __shfl_xor_sync(~0u, m0, 1)); m0 = fmaxf(m0, __shfl_xor_sync(~0u, m0, 2));
  m1 = fmaxf(m1, __shfl_xor_sync(~0u, m1, 1)); m1 = fmaxf(m1, __shfl_xor_sync(~0u, m1, 2));
  SoftmaxRow r;
  r.mc0 = fmaf(m0, SM_C, 56.f); r.mc1 = fmaf(m1, SM_C, 56.f);
  r.a = SM_C * (1.f / 253.f); r.b0 = (125.f - r.mc0) * (1.f / 253.f); r.b1 = (125.f - r.mc1) * (1.f / 253.f);
  return r;
}

__device__ __forceinline__ void attention(Cons& c, const uint32_t (&qf)[4][8]) {
  const uint32_t base0 = (c.sb >> 4) | (1u << 16);
  constexpr uint32_t STG = 2 * SLOT >> 4;
  constexpr int P_FIRST = ORD_A & 15, P_LAST = (ORD_A >> 12) & 15;
  float S0[32], S1[32], Oa[20];
  uint32_t P0[16], P1[16], q[8], qn[8];
  auto qka = [&](float (&S)[32], const uint32_t (&a)[8], uint32_t lo) { wgmma_m64n64k16_rs<0>(S, a[0], a[1], a[2], a[3], dsc(lo, HI_64), 0); };
  auto qkb = [&](float (&S)[32], const uint32_t (&a)[8], uint32_t lo) { wgmma_m64n64k16_rs<0>(S, a[4], a[5], a[6], a[7], dsc(lo + 2, HI_64), 1); };
  auto pv = [&](uint32_t (&P)[16], int kk, uint32_t lo, int acc) { wgmma_m64n40k16_rs<0>(Oa, P[4 * kk], P[4 * kk + 1], P[4 * kk + 2], P[4 * kk + 3], dsc(lo + kk * 2, HI_128), acc); };
#pragma unroll
  for (int i = 0; i < 8; i++) q[i] = qf[0][i];
#pragma unroll
  for (int i = 0; i < 20; i++) Oa[i] = 0.f;
  c.wait_full(2 * P_FIRST);
  fence_regs(Oa);
  wg_fence(); qka(S0, q, base0 + P_FIRST * STG); qkb(S0, q, base0 + P_FIRST * STG); wg_commit(); wg_wait<0>();
  fence_regs(S0);
  SoftmaxRow r = softmax_offsets(S0);
#pragma unroll 1
  for (int hh = 0; hh < 4; hh++) {
#pragma unroll
    for (int i = 0; i < 8; i++) qn[i] = hh == 0 ? qf[1][i] : hh == 1 ? qf[2][i] : qf[3][i];
#pragma unroll
    for (int i = 12; i < 16; i++) P1[i] = 0u;
    auto tile = [&](auto ST, int turn) {
      constexpr int st = decltype(ST)::value;
      constexpr int pc = (ORD_A >> (4 * st)) & 15, pp = (ORD_A >> (4 * ((st + 3) & 3))) & 15, pn = (ORD_A >> (4 * ((st + 1) & 3))) & 15;
      const bool first = (st == 0) && (turn == 0), head_end = (st == 3) && (turn == 3), last = head_end && hh == 3;
      const uint32_t kb = base0 + pc * STG, vb = kb + 512;
      const uint32_t vprev = first ? vb : base0 + pp * STG + 512;
      const uint32_t kn = last ? kb : base0 + pn * STG;
      const uint32_t nbar = c.sb + OFF_FULL + 16 * pn, npar = (c.fmask >> (2 * pn)) & 1;
      bool ok = true;
      if (!last) { ok = mbar_try(nbar, npar); c.fmask ^= 1u << (2 * pn); }
      softmax_grp<0>(S0, P0, r); fence_regs(S1); fence4(P1 + 12); wg_fence(); pv(P1, 3, vprev + 320, !first); qka(S1, q, kb + 256);
      softmax_grp<1>(S0, P0, r); fence4(P0); wg_fence(); qkb(S1, q, kb + 256); wg_commit(); pv(P0, 0, vb, 1);
      softmax_grp<2>(S0, P0, r); fence4(P0 + 4); wg_fence(); pv(P0, 1, vb, 1);
      softmax_grp<3>(S0, P0, r); fence4(P0 + 8); wg_fence(); pv(P0, 2, vb, 1); wg_commit();
      wg_wait<1>(); fence_regs(S1); fence_regs(P1);
      if (!first) c.release(2 * pp);
      if (!ok) mbar_wait(nbar, npar);
      if (st == 3 && head_end) {
#pragma unroll
        for (int i = 0; i < 8; i++) q[i] = qn[i];
      }
      softmax_grp<0>(S1, P1, r); fence_regs(S0); fence4(P0 + 12); fence_regs(q); wg_fence(); pv(P0, 3, vb, 1); qka(S0, q, kn);
      softmax_grp<1>(S1, P1, r); fence4(P1); wg_fence(); qkb(S0, q, kn); wg_commit(); pv(P1, 0, vb + 320, 1);
      softmax_grp<2>(S1, P1, r); fence4(P1 + 4); wg_fence(); pv(P1, 1, vb + 320, 1);
      softmax_grp<3>(S1, P1, r); fence4(P1 + 8); wg_fence(); pv(P1, 2, vb + 320, 1); wg_commit();
      wg_wait<1>(); fence_regs(S0); fence_regs(P0);
    };
#pragma unroll 1
    for (int turn = 0; turn < 4; turn++) { tile(IC<0>{}, turn); tile(IC<1>{}, turn); tile(IC<2>{}, turn); tile(IC<3>{}, turn); }
    fence4(P1 + 12); wg_fence(); pv(P1, 3, base0 + P_LAST * STG + 512 + 320, 1); wg_commit();
    r = softmax_offsets(S0);
    wg_wait<0>(); fence_regs(Oa);
    c.release(2 * P_LAST);
    float l0 = __shfl_sync(~0u, Oa[16], c.lane & ~3), l1 = __shfl_sync(~0u, Oa[18], c.lane & ~3);
    bool bad = !(l0 < 1e37f) || !(l1 < 1e37f);
#pragma unroll
    for (int i = 0; i < 16; i++) bad |= !(fabsf(Oa[i]) <= 3.0e38f);
    if (__any_sync(~0u, bad)) {
      uint32_t qh[8];
#pragma unroll
      for (int i = 0; i < 8; i++) qh[i] = hh == 0 ? qf[0][i] : hh == 1 ? qf[1][i] : hh == 2 ? qf[2][i] : qf[3][i];
      attention_exact(qh, Oa, l0, l1, c.lane);
    }
    const float i0 = __frcp_rn(l0), i1 = __frcp_rn(l1);
#pragma unroll
    for (int h2 = 0; h2 < 2; h2++) {
      const int a = 8 * h2;
      stsm4(c.stg_addr(hh * 2 + h2), pack_bf16(Oa[a] * i0, Oa[a + 1] * i0), pack_bf16(Oa[a + 2] * i1, Oa[a + 3] * i1),
            pack_bf16(Oa[a + 4] * i0, Oa[a + 5] * i0), pack_bf16(Oa[a + 6] * i1, Oa[a + 7] * i1));
    }
    if (hh & 1) c.stg_publish();
  }
}

template <int NB>
__device__ __forceinline__ void glu_epilogue(Cons& c, const float (&acc)[NB * 64]) {
  c.stg_acquire();
#pragma unroll
  for (int b = 0; b < NB; b++)
#pragma unroll
    for (int cb = 0; cb < 4; cb++) {
      uint32_t v[4];
#pragma unroll
      for (int e = 0; e < 4; e++) {
        const int ig = b * 32 + cb * 8 + 2 * e, iu = ig + NB * 32;
        const float h0 = fmaf(tanh_fast(0.5f * acc[ig]), 0.5f, 0.5f) * acc[iu];
        const float h1 = fmaf(tanh_fast(0.5f * acc[ig + 1]), 0.5f, 0.5f) * acc[iu + 1];
        v[e] = pack_bf16(h0, h1);
      }
      stsm4(c.stg_addr(b * 4 + cb), v[0], v[1], v[2], v[3]);
    }
  c.stg_publish();
}

__device__ __forceinline__ float silu_bf16(float v) { return round_bf16(__fdividef(v, 1.f + __expf(-v))); }
__device__ __forceinline__ uint4 lds128(uint32_t a) {
  uint4 v;
  asm volatile("ld.shared.v4.b32 {%0,%1,%2,%3}, [%4];" : "=r"(v.x), "=r"(v.y), "=r"(v.z), "=r"(v.w) : "r"(a));
  return v;
}
__device__ __forceinline__ void unpack8(const uint4& v, float (&f)[8]) {
  f[0] = bf_lo(v.x); f[1] = bf_hi(v.x); f[2] = bf_lo(v.y); f[3] = bf_hi(v.y);
  f[4] = bf_lo(v.z); f[5] = bf_hi(v.z); f[6] = bf_lo(v.w); f[7] = bf_hi(v.w);
}

__device__ __forceinline__ void consumer_role(const Params& p, uint32_t sb, int cw, int mt, int j, int cta) {
  const int tid = threadIdx.x - 128, lane = tid & 31, warp8 = tid >> 5;
  Cons c{sb, 0u, 0u, cw, lane, warp8 & 3, (tid & 127) == 0};
  const bool lead0 = tid == 0;

  {
    uint4 xv[2][4];
    float cv[8];
    const int rg = tid >> 1, hf = tid & 1;
    const int r0 = mt * 128 + j * 16 + warp8 * 2;
#pragma unroll
    for (int i = 0; i < 8; i++) cv[i] = __bfloat162float(p.c[rg + 128 * i]);
#pragma unroll
    for (int rr = 0; rr < 2; rr++)
#pragma unroll
      for (int i = 0; i < 4; i++) xv[rr][i] = __ldg(reinterpret_cast<const uint4*>(p.x + (size_t)(r0 + rr) * DM + i * 256 + lane * 8));
    bar_sync(0, NTHREADS);
#pragma unroll
    for (int i = 0; i < 8; i++) cv[i] = silu_bf16(cv[i]);
    float acc[8] = {};

    mbar_wait(sb + OFF_AUX, 0);

#pragma unroll
    for (int i = 0; i < 8; i++) {
      float f[8]; unpack8(lds128(sb + OFF_STG + (rg + 128 * i) * 32 + hf * 16), f);
#pragma unroll
      for (int e = 0; e < 8; e++) acc[e] = fmaf(cv[i], f[e], acc[e]);
    }
#pragma unroll
    for (int e = 0; e < 8; e++)
#pragma unroll
      for (int o = 2; o < 32; o <<= 1) acc[e] += __shfl_xor_sync(~0u, acc[e], o);
    if (lane < 2)
#pragma unroll
      for (int e = 0; e < 8; e++) sts32(sb + OFF_VEC + (warp8 * 16 + lane * 8 + e) * 4, acc[e]);

    bar_sync(1, 256);
    if (tid < 16) {
      float s = 0.f;
#pragma unroll
      for (int w = 0; w < 8; w++) s += lds32(sb + OFF_VEC + (w * 16 + tid) * 4);
      const float nxt = __shfl_down_sync(0xffffu, s, 1);
      if ((tid & 1) == 0)
        asm volatile("st.relaxed.gpu.global.u32 [%0], %1;" ::"l"(g_mod1 + cta * 8 + (tid >> 1)), "r"(~pack_bf16(s, nxt)) : "memory");
    }

    float mean[2], rstd[2];
#pragma unroll
    for (int rr = 0; rr < 2; rr++) {
      float s = 0.f;
#pragma unroll
      for (int i = 0; i < 4; i++) { float f[8]; unpack8(xv[rr][i], f);
#pragma unroll
        for (int e = 0; e < 8; e++) s += f[e]; }
#pragma unroll
      for (int o = 1; o < 32; o <<= 1) s += __shfl_xor_sync(~0u, s, o);
      mean[rr] = s * (1.f / DM);
      float v = 0.f;
#pragma unroll
      for (int i = 0; i < 4; i++) { float f[8]; unpack8(xv[rr][i], f);
#pragma unroll
        for (int e = 0; e < 8; e++) { const float d = f[e] - mean[rr]; v = fmaf(d, d, v); } }
#pragma unroll
      for (int o = 1; o < 32; o <<= 1) v += __shfl_xor_sync(~0u, v, o);
      rstd[rr] = rsqrtf(v * (1.f / DM) + 1e-5f);
    }

    sts128(sb + OFF_STG + tid * 16, ld_bf16x8_valid(g_mod1 + tid * 4));
    bar_sync(1, 256);
    if (lead0) mbar_arrive(sb + OFF_AUX + 32);

    uint4 mv[4][2];
#pragma unroll
    for (int i = 0; i < 4; i++) {
      const uint32_t a = sb + OFF_STG + (i * 256 + lane * 8) * 2;
      mv[i][0] = lds128(a); mv[i][1] = lds128(a + 2048);
    }
    bar_sync(1, 256);
#pragma unroll
    for (int i = 0; i < 4; i++) {
      float sa[8], ca[8];
      unpack8(mv[i][0], sa); unpack8(mv[i][1], ca);
#pragma unroll
      for (int rr = 0; rr < 2; rr++) {
        float f[8]; unpack8(xv[rr][i], f);
        float h[8];
#pragma unroll
        for (int e = 0; e < 8; e++) h[e] = fmaf((f[e] - mean[rr]) * rstd[rr], 1.f + ca[e], sa[e]);
        const uint4 o = make_uint4(pack_bf16(h[0], h[1]), pack_bf16(h[2], h[3]), pack_bf16(h[4], h[5]), pack_bf16(h[6], h[7]));
        *reinterpret_cast<uint4*>(g_h1 + (size_t)(r0 + rr) * DM + i * 256 + lane * 8) = o;
        const int row = warp8 * 2 + rr;
        sts128(sb + OFF_STG + (i * 4 + (lane >> 3)) * 2048 + row * 128 + (((lane & 7) ^ (row & 7)) << 4), o);
      }
    }

    fence_async_smem();
    fence_async_global();
    bar_sync(1, 256);

    if (lead0) mbar_arrive(sb + OFF_AUX + 16);
  }

  reg_alloc<240>();

  {
    float d[8];
    const uint32_t abase = (sb >> 4) | ((SLOT >> 4) << 16), bbase = ((sb + OFF_STG) >> 4) | (1u << 16);
#pragma unroll 1
    for (int q = 0; q < 4; q++) {
      c.wait_full(2 * q);
      if (cw == 0) {
        wg_fence();
#pragma unroll
        for (int k = 0; k < 16; k++)
          wgmma_m64n16k16_ss<1, 0>(d, dsc(abase + q * 2 * (SLOT >> 4) + k * 64, HI_64),
                                   dsc(bbase + (q * 4 + (k >> 2)) * 128 + (k & 3) * 2, HI_128), (q | k) != 0);
        wg_commit(); wg_wait<0>();
      }
      c.release(2 * q);
    }

    if (cw == 0) {
      fence_regs(d);
      const int tok0 = mt * 128 + j * 16, g = lane >> 2, t = lane & 3;
      if (c.warp < 2) {
#pragma unroll
        for (int e = 0; e < 8; e++) {
          const int m = c.warp * 16 + g + ((e >> 1) & 1) * 8, n = (e >> 2) * 8 + 2 * t + (e & 1);
          g_k[(tok0 + n) * 32 + m] = __float2bfloat16(d[e]);
        }
      } else {
#pragma unroll
        for (int e = 0; e < 4; e++) {
          const int m = (c.warp - 2) * 16 + g + (e & 1) * 8, n = (e >> 1) * 8 + 2 * t;
          *reinterpret_cast<uint32_t*>(g_vt + m * SEQ + tok0 + n) = pack_bf16(d[2 * e], d[2 * e + 1]);
        }
        if (c.warp == 2 && lane < 16) {
          const uint32_t one = lane < 2 ? 0x3f803f80u : 0u;
          *reinterpret_cast<uint4*>(g_vt + (32 + (lane >> 1)) * SEQ + tok0 + (lane & 1) * 8) = make_uint4(one, one, one, one);
        }
      }
      fence_async_global();
      bar_sync(2, 128);
      if (c.leader) mbar_arrive(sb + OFF_AUX + 24);
    }
  }

  uint32_t qf[4][8];
  {
    float acc[64];
    gemm_loop<128, 2, ORD_Q, 6>(c, acc, 16, 0);
#pragma unroll
    for (int h = 0; h < 4; h++)
#pragma unroll
      for (int i = 0; i < 8; i++) qf[h][i] = pack_bf16(acc[16 * h + 2 * i], acc[16 * h + 2 * i + 1]);
  }

  attention(c, qf);
  bar_sync(2 + cw, 128);

  const int g8 = lane >> 2, t4 = lane & 3;
  uint32_t x1p[32];
  {
    float acc[64];
    c.wait_full(10);
    gemm_loop<128, 2, ORD_O, 5>(c, acc, 16, 2);

    mbar_wait(sb + OFF_AUX + 8, 0);
    float s0 = 0.f, s1 = 0.f;
    {
      const int r = cw * 64 + c.warp * 16 + (lane & 7) + ((lane >> 3) & 1) * 8;
#pragma unroll
      for (int cb = 0; cb < 8; cb++) {
        uint32_t xin[4];
        const int chunk = (cb & 3) * 2 + (lane >> 4);
        ldsm4(sb + (10 + (cb >> 2)) * SLOT + r * 128 + ((chunk ^ (r & 7)) << 4), xin[0], xin[1], xin[2], xin[3]);
#pragma unroll
        for (int h = 0; h < 2; h++) {
          const int nb = 2 * cb + h;
          const float2 ga = lds64(sb + OFF_VEC + (nb * 8 + t4 * 2) * 4);
          acc[4 * nb] = fmaf(ga.x, acc[4 * nb], bf_lo(xin[2 * h]));
          acc[4 * nb + 1] = fmaf(ga.y, acc[4 * nb + 1], bf_hi(xin[2 * h]));
          acc[4 * nb + 2] = fmaf(ga.x, acc[4 * nb + 2], bf_lo(xin[2 * h + 1]));
          acc[4 * nb + 3] = fmaf(ga.y, acc[4 * nb + 3], bf_hi(xin[2 * h + 1]));
          s0 += acc[4 * nb] + acc[4 * nb + 1];
          s1 += acc[4 * nb + 2] + acc[4 * nb + 3];
        }
      }
    }
    __syncwarp();
    c.release(10);
    s0 += __shfl_xor_sync(~0u, s0, 1); s0 += __shfl_xor_sync(~0u, s0, 2);
    s1 += __shfl_xor_sync(~0u, s1, 1); s1 += __shfl_xor_sync(~0u, s1, 2);
    const float pm0 = s0 * (1.f / 128), pm1 = s1 * (1.f / 128);
    float v0 = 0.f, v1 = 0.f;
#pragma unroll
    for (int nb = 0; nb < 16; nb++) {
      float d;
      d = acc[4 * nb] - pm0; v0 = fmaf(d, d, v0); d = acc[4 * nb + 1] - pm0; v0 = fmaf(d, d, v0);
      d = acc[4 * nb + 2] - pm1; v1 = fmaf(d, d, v1); d = acc[4 * nb + 3] - pm1; v1 = fmaf(d, d, v1);
    }
    v0 += __shfl_xor_sync(~0u, v0, 1); v0 += __shfl_xor_sync(~0u, v0, 2);
    v1 += __shfl_xor_sync(~0u, v1, 1); v1 += __shfl_xor_sync(~0u, v1, 2);
    const int lrow = cw * 64 + c.warp * 16 + g8;
    if (t4 == 0) {
      st_tagged2(&g_stats[(mt * 8 + j) * 128 + lrow], pm0, v0);
      st_tagged2(&g_stats[(mt * 8 + j) * 128 + lrow + 8], pm1, v1);
    }
    float2 sh[16], sc[16];
#pragma unroll
    for (int nb = 0; nb < 16; nb++) {
      x1p[2 * nb] = pack_bf16(acc[4 * nb], acc[4 * nb + 1]);
      x1p[2 * nb + 1] = pack_bf16(acc[4 * nb + 2], acc[4 * nb + 3]);
      sh[nb] = lds64(sb + OFF_VEC + 512 + (nb * 8 + t4 * 2) * 4);
      sc[nb] = lds64(sb + OFF_VEC + 1024 + (nb * 8 + t4 * 2) * 4);
    }
    __nanosleep(250);
    float mu[2], rs[2];
    uint2 sv[4];
    {
      const uint2* q = &g_stats[(mt * 8 + 2 * t4) * 128 + lrow];
      ld_tagged2x4(q, q + 128, q + 8, q + 136, sv);
    }
#pragma unroll
    for (int rr = 0; rr < 2; rr++) {
      const float2 a = make_float2(__uint_as_float(sv[2 * rr].x), __uint_as_float(sv[2 * rr].y));
      const float2 b = make_float2(__uint_as_float(sv[2 * rr + 1].x), __uint_as_float(sv[2 * rr + 1].y));
      float m = a.x + b.x;
      m += __shfl_xor_sync(~0u, m, 1); m += __shfl_xor_sync(~0u, m, 2);
      m *= 0.125f;
      float q = a.y + b.y + 128.f * ((a.x - m) * (a.x - m) + (b.x - m) * (b.x - m));
      q += __shfl_xor_sync(~0u, q, 1); q += __shfl_xor_sync(~0u, q, 2);
      mu[rr] = m; rs[rr] = rsqrtf(q * (1.f / DM) + 1e-5f);
    }
    const float nm[2] = {-mu[0] * rs[0], -mu[1] * rs[1]};

    c.stg_acquire();
#pragma unroll
    for (int cb = 0; cb < 8; cb++) {
      uint32_t v[4];
#pragma unroll
      for (int h = 0; h < 2; h++) {
        const int nb = 2 * cb + h;
        v[2 * h] = pack_bf16(fmaf(fmaf(acc[4 * nb], rs[0], nm[0]), sc[nb].x, sh[nb].x), fmaf(fmaf(acc[4 * nb + 1], rs[0], nm[0]), sc[nb].y, sh[nb].y));
        v[2 * h + 1] = pack_bf16(fmaf(fmaf(acc[4 * nb + 2], rs[1], nm[1]), sc[nb].x, sh[nb].x), fmaf(fmaf(acc[4 * nb + 3], rs[1], nm[1]), sc[nb].y, sh[nb].y));
      }
      stsm4(c.stg_addr(cb), v[0], v[1], v[2], v[3]);
    }
    c.stg_publish();
    bar_sync(2 + cw, 128);
  }

#pragma unroll 1
  for (int t = 0; t < 3; t++) {
    float acc[128];
    gemm_loop<256, 3, ORD_G, 4>(c, acc, 16, t == 0 ? 2 : 0);
    glu_epilogue<2>(c, acc);
  }
  {
    float acc[64];
    gemm_loop<128, 2, ORD_D, 6>(c, acc, 16, 0);
    glu_epilogue<1>(c, acc);
  }

  {
    float acc[64];
    gemm_loop<128, 2, ORD_D, 6>(c, acc, 56, 0, 4);

    c.stg_acquire();
#pragma unroll
    for (int cb = 0; cb < 8; cb++) {
      uint32_t v[4];
#pragma unroll
      for (int h = 0; h < 2; h++) {
        const int nb = 2 * cb + h;
        const float2 gb = lds64(sb + OFF_VEC + 1536 + (nb * 8 + t4 * 2) * 4);
        v[2 * h] = pack_bf16(fmaf(gb.x, acc[4 * nb], bf_lo(x1p[2 * nb])), fmaf(gb.y, acc[4 * nb + 1], bf_hi(x1p[2 * nb])));
        v[2 * h + 1] = pack_bf16(fmaf(gb.x, acc[4 * nb + 2], bf_lo(x1p[2 * nb + 1])), fmaf(gb.y, acc[4 * nb + 3], bf_hi(x1p[2 * nb + 1])));
      }
      stsm4(c.stg_addr(cb), v[0], v[1], v[2], v[3]);
    }
    c.stg_publish();
  }
  if (tid < 8) g_mod1[cta * 8 + tid] = 0u;
  if (tid < 128) g_stats[(mt * 8 + j) * 128 + tid] = make_uint2(0u, 0u);
}

__device__ __forceinline__ void helper_role(const Params& p, uint32_t sb, int hidx) {
  constexpr int HST = 6, ROWS = 16;
  const int tid = threadIdx.x;
  const uint32_t full = sb + OFF_FULL, empty = sb + OFF_EMPTY, sil = sb + OFF_STG;
  if (tid == 0) {
    for (int s = 0; s < HST; s++) { mbar_init(full + 8 * s, 1); mbar_init(empty + 8 * s, 8); }
    asm volatile("fence.mbarrier_init.release.cluster;" ::: "memory");
  }
  for (int i = tid; i < DM; i += NTHREADS) sts32(sil + i * 4, silu_bf16(__bfloat162float(p.c[i])));
  __syncthreads();
  const bf16* src = p.wmod + 2 * DM + hidx * 1024;
  if (tid >= 256 && tid < 288) {
    if (elect_one()) for (int i = 0; i < DM / ROWS; i++) {
      const int s = i % HST;
      mbar_wait(empty + 8 * s, ((i / HST) & 1) ^ 1);
      mbar_expect_tx(full + 8 * s, ROWS * 2048);
      for (int r = 0; r < ROWS; r++)
        asm volatile("cp.async.bulk.shared::cluster.global.mbarrier::complete_tx::bytes [%0], [%1], 2048, [%2];"
                     ::"r"(sb + s * 32768 + r * 2048), "l"(src + (size_t)(i * ROWS + r) * MODN), "r"(full + 8 * s) : "memory");
    }
  } else if (tid < 256) {
    const int cg = tid & 127, rh = tid >> 7;
    float acc[8] = {};
#pragma unroll 1
    for (int i = 0; i < DM / ROWS; i++) {
      const int s = i % HST;
      mbar_wait(full + 8 * s, (i / HST) & 1);
#pragma unroll
      for (int r = 0; r < ROWS / 2; r++) {
        const int row = rh * (ROWS / 2) + r;
        uint4 w;
        asm volatile("ld.shared.v4.b32 {%0,%1,%2,%3}, [%4];" : "=r"(w.x), "=r"(w.y), "=r"(w.z), "=r"(w.w) : "r"(sb + s * 32768 + row * 2048 + cg * 16));
        const float sv = lds32(sil + (i * ROWS + row) * 4);
        float f[8]; unpack8(w, f);
#pragma unroll
        for (int e = 0; e < 8; e++) acc[e] = fmaf(sv, f[e], acc[e]);
      }
      __syncwarp();
      if ((tid & 31) == 0) mbar_arrive(empty + 8 * s);
    }
    const uint32_t red = sil + 4096;
    if (rh == 1)
#pragma unroll
      for (int e = 0; e < 8; e++) sts32(red + (cg * 8 + e) * 4, acc[e]);
    bar_sync(1, 256);
    if (rh == 0)
#pragma unroll
      for (int e = 0; e < 8; e++) g_mod[2 * DM + hidx * 1024 + cg * 8 + e] = round_bf16(acc[e] + lds32(red + (cg * 8 + e) * 4));
    bar_sync(1, 256);
    if (tid == 0) flag_signal(F_MOD2);
  }
}

__global__ void __launch_bounds__(NTHREADS, 1) adaln_block_kernel(const __grid_constant__ Params p) {
  extern __shared__ __align__(1024) uint8_t smem[];
  const uint32_t sb = __shfl_sync(~0u, opaque((uint32_t)__cvta_generic_to_shared(smem)), 0);
  const int tid = threadIdx.x, cta = blockIdx.x;
  const int wg = __shfl_sync(~0u, tid >> 7, 0);
  if (cta >= NWORK) {
    helper_role(p, sb, cta - NWORK);
  } else {
    const int grp = cta >> 3, r = cta & 7;
    const int mt = (grp >> 2) * 4 + (r >> 1), j = (grp & 3) * 2 + (r & 1);
    if (wg == 0) {
      const int warp = __shfl_sync(~0u, tid >> 5, 0);
      if (warp == 0) {
        if (elect_one()) {
          mbar_init(sb + OFF_AUX, 1);
          asm volatile("fence.mbarrier_init.release.cluster;" ::: "memory");
          mbar_expect_tx(sb + OFF_AUX, 32768);
          for (int q = 0; q < 4; q++) tma_load(sb + OFF_STG + q * 8192, &p.wm, sb + OFF_AUX, cta * 16, q * 256);
        }
      } else if (warp == 1) {
        const int l = tid - 32;
        if (l < (int)NSLOT) { mbar_init(sb + OFF_FULL + 8 * l, 1); mbar_init(sb + OFF_EMPTY + 8 * l, 8); }
        else if (l < 14) { mbar_init(sb + OFF_STF + 8 * (l - 12), 4); mbar_init(sb + OFF_STE + 8 * (l - 12), 1); }
        else if (l < 18) mbar_init(sb + OFF_AUX + 8 * (l - 13), 1);
        asm volatile("fence.mbarrier_init.release.cluster;" ::: "memory");
      }
      __syncwarp();
      bar_sync(0, NTHREADS);
      reg_dealloc<24>();
      if (warp == 0) { if (elect_one()) producer_role(p, sb, mt, j, cta); }
      else if (warp == 1) { if (elect_one()) store_role(p, sb, mt, j); }
      else if (warp == 3) signal_role(sb, mt, j);
    } else {
      consumer_role(p, sb, wg - 1, mt, j, cta);
    }
  }
  __syncthreads();

  if (cta == 0 && tid == 0) *flag_ptr(F_EPOCH) = load_epoch();
}

typedef CUresult (*EncodeFn)(CUtensorMap*, CUtensorMapDataType, cuuint32_t, void*, const cuuint64_t*, const cuuint64_t*, const cuuint32_t*,
                             const cuuint32_t*, CUtensorMapInterleave, CUtensorMapSwizzle, CUtensorMapL2promotion, CUtensorMapFloatOOBfill);

static void make_map(EncodeFn enc, CUtensorMap* m, const void* ptr, uint64_t inner, uint64_t outer, uint32_t bi, uint32_t bo, CUtensorMapSwizzle sw) {
  cuuint64_t dims[2] = {inner, outer}, strides[1] = {inner * 2};
  cuuint32_t box[2] = {bi, bo}, es[2] = {1, 1};
  enc(m, CU_TENSOR_MAP_DATA_TYPE_BFLOAT16, 2, const_cast<void*>(ptr), dims, strides, box, es, CU_TENSOR_MAP_INTERLEAVE_NONE, sw,
      CU_TENSOR_MAP_L2_PROMOTION_L2_128B, CU_TENSOR_MAP_FLOAT_OOB_FILL_NONE);
}
static void make_map3(EncodeFn enc, CUtensorMap* m, const void* ptr, uint64_t cols, uint64_t rows) {
  cuuint64_t dims[3] = {64, rows, cols / 64}, strides[2] = {cols * 2, 128};
  cuuint32_t box[3] = {64, 64, 2}, es[3] = {1, 1, 1};
  enc(m, CU_TENSOR_MAP_DATA_TYPE_BFLOAT16, 3, const_cast<void*>(ptr), dims, strides, box, es, CU_TENSOR_MAP_INTERLEAVE_NONE,
      CU_TENSOR_MAP_SWIZZLE_128B, CU_TENSOR_MAP_L2_PROMOTION_L2_128B, CU_TENSOR_MAP_FLOAT_OOB_FILL_NONE);
}
template <typename T> static void* sym_addr(const T& s) { void* a = nullptr; cudaGetSymbolAddress(&a, s); return a; }

extern "C" void kernel_launch(void* const* d_in, const int* in_sizes, int n_in, void* d_out, int out_size) {
  void* fn = nullptr;
  cudaDriverEntryPointQueryResult qr;
  cudaGetDriverEntryPoint("cuTensorMapEncodeTiled", &fn, cudaEnableDefault, &qr);
  EncodeFn enc = (EncodeFn)fn;
  Params p;
  const CUtensorMapSwizzle S128 = CU_TENSOR_MAP_SWIZZLE_128B, S64 = CU_TENSOR_MAP_SWIZZLE_64B;
  make_map3(enc, &p.wq, d_in[1], DM, DM);
  make_map3(enc, &p.wo, d_in[4], DM, DM);
  make_map3(enc, &p.wd, d_in[8], DM, FF);
  make_map3(enc, &p.wg2, d_in[6], FF, DM);
  make_map3(enc, &p.wu2, d_in[7], FF, DM);
  make_map(enc, &p.wg1, d_in[6], FF, DM, 64, 64, S128);
  make_map(enc, &p.wu1, d_in[7], FF, DM, 64, 64, S128);
  make_map(enc, &p.wk, d_in[2], 32, DM, 32, 256, S64);
  make_map(enc, &p.wv, d_in[3], 32, DM, 32, 256, S64);
  make_map(enc, &p.h1, sym_addr(g_h1), DM, SEQ, 64, 128, S128);
  make_map(enc, &p.ob, sym_addr(g_o), DM, SEQ, 64, 128, S128);
  make_map(enc, &p.h2, sym_addr(g_h2), DM, SEQ, 64, 128, S128);
  make_map(enc, &p.hh, sym_addr(g_hh), FF, SEQ, 64, 128, S128);
  make_map(enc, &p.xm, d_in[0], DM, SEQ, 64, 128, S128);
  make_map(enc, &p.obs, sym_addr(g_o), DM, SEQ, 64, 64, S128);
  make_map(enc, &p.h2s, sym_addr(g_h2), DM, SEQ, 64, 64, S128);
  make_map(enc, &p.hhs, sym_addr(g_hh), FF, SEQ, 64, 64, S128);
  make_map(enc, &p.outs, d_out, DM, SEQ, 64, 64, S128);
  make_map(enc, &p.kb, sym_addr(g_k), 32, SEQ, 32, 128, S64);
  make_map(enc, &p.vt, sym_addr(g_vt), SEQ, 40, 64, 40, S128);
  make_map(enc, &p.wm, d_in[10], MODN, DM, 16, 256, CU_TENSOR_MAP_SWIZZLE_NONE);
  p.x = (const bf16*)d_in[0];
  p.c = (const bf16*)d_in[9];
  p.wmod = (const bf16*)d_in[10];
  cudaFuncSetAttribute(adaln_block_kernel, cudaFuncAttributeMaxDynamicSharedMemorySize, SMEM_BYTES);
  adaln_block_kernel<<<NCTA, NTHREADS, SMEM_BYTES>>>(p);
}
```
